```python
import torch

def _softmax(x, axis=-1):
    return torch.softmax(x, dim=axis)
def _gelu(x):
    return torch.nn.functional.gelu(x, approximate="tanh")
def _silu(x):
    return torch.nn.functional.silu(x)
def _sigmoid(x):
    return torch.sigmoid(x)
def _layernorm(x, axis=-1, eps=1e-5):
    m = x.mean(dim=axis, keepdim=True)
    v = x.var(dim=axis, keepdim=True, unbiased=False)
    return (x - m) / torch.sqrt(v + eps)
def _scatter_add(tgt, idx, src, axis=0):
    return tgt.clone().index_add_(axis, idx, src)
def _segment_sum(src, seg, n):
    out = torch.zeros((n,) + src.shape[1:], dtype=src.dtype)
    return out.index_add_(0, seg, src)
def _pad(x, pw):
    flat = tuple(v for pair in reversed(pw) for v in pair)
    return torch.nn.functional.pad(x, flat)

kernel_name = 'recurrent_scan__compressed_kv_cla__swiglu_ffn__prompt'

def setup_inputs():

    _w = (lambda a: (lambda t: t.to(torch.bfloat16) if t.is_floating_point() else t)(torch.as_tensor(a)))
    def _A_setup():
        B, H, Sq, Sk, D, M = 1, 16, 2048, 2048, 256, 448
        Dc = 4 * D
        return {
            "x": _w((lambda *s: torch.randn(*s, dtype=torch.bfloat16) * 0.05)(B, Sq, M)),
            "c_kv": _w((lambda *s: torch.randn(*s, dtype=torch.bfloat16) * 0.2)(B, Sk, Dc)),
            "w_q": _w((lambda *s: torch.randn(*s, dtype=torch.bfloat16) * 3.2)(M, H, D) * (M ** -0.5)),
            "w_uk": _w((lambda *s: torch.randn(*s, dtype=torch.bfloat16) * 3.2)(Dc, H, D) * (Dc ** -0.5)),
            "w_uv": _w((lambda *s: torch.randn(*s, dtype=torch.bfloat16) * 0.2)(Dc, H, D) * (Dc ** -0.5)),
            "w_o": _w((lambda *s: torch.randn(*s, dtype=torch.bfloat16) * 0.2)(H, D, M) * ((H * D) ** -0.5)),
        }
    _A_in = _A_setup()

    def _B_setup():
        B, S, D, F = 1, 2048, 448, 1792
        return {
            "x": _w((lambda *s: torch.randn(*s, dtype=torch.bfloat16) * 0.05)(B, S, D)),
            "w_gate": _w((lambda *s: torch.randn(*s, dtype=torch.bfloat16) * 0.1)(D, F)),
            "w_up": _w((lambda *s: torch.randn(*s, dtype=torch.bfloat16) * 0.1)(D, F)),
            "w_down": _w((lambda *s: torch.randn(*s, dtype=torch.bfloat16) * 0.1)(F, D)),
        }
    _B_in = _B_setup()

    return {
        "A_x": _A_in["x"],
        "A_c_kv": _A_in["c_kv"],
        "A_w_q": _A_in["w_q"],
        "A_w_uk": _A_in["w_uk"],
        "A_w_uv": _A_in["w_uv"],
        "A_w_o": _A_in["w_o"],
        "B_x": _B_in["x"],
        "B_w_gate": _B_in["w_gate"],
        "B_w_up": _B_in["w_up"],
        "B_w_down": _B_in["w_down"],
    }

def reference(A_x, A_c_kv, A_w_q, A_w_uk, A_w_uv, A_w_o, B_x, B_w_gate, B_w_up, B_w_down):
    def _A_ref(x, c_kv, w_q, w_uk, w_uv, w_o):
        B, Sq, M = x.shape[0], x.shape[1], x.shape[2]
        Sk = c_kv.shape[1]
        H, D = w_q.shape[1], w_q.shape[2]
        q = torch.einsum("bqm,mhd->bhqd", x, w_q)
        k = torch.einsum("bkc,chd->bhkd", c_kv, w_uk)
        v = torch.einsum("bkc,chd->bhkd", c_kv, w_uv)
        scores = torch.einsum("bhqd,bhkd->bhqk", q, k) * (D ** -0.5)
        off = Sk - Sq
        qi = torch.arange(Sq)[:, None]
        kj = torch.arange(Sk)[None, :]
        cmask = kj <= (qi + off)
        scores = torch.where(cmask[None, None], scores, -1e9)
        p = _softmax(scores, axis=-1)
        ctx = torch.einsum("bhqk,bhkd->bhqd", p, v)
        return torch.einsum("bhqd,hdm->bqm", ctx, w_o)

    def _B_ref(x, w_gate, w_up, w_down):
        g = _silu(x @ w_gate)
        u = x @ w_up
        return (g * u) @ w_down

    x = A_x
    xn = _layernorm(x, axis=-1)
    s = _A_ref(xn, A_c_kv, A_w_q, A_w_uk, A_w_uv, A_w_o)
    g = _silu(_B_ref(xn, B_w_gate, B_w_up, B_w_down))
    return x + s * g
```

```cpp
#include <cuda_runtime.h>
#include <cuda_bf16.h>
#include <cuda.h>
#include <stdint.h>

typedef __nv_bfloat16 bf16;
#define SALT 0

constexpr int SEQ = 2048, DM = 448, DC = 1024, NH = 16, HD = 256, FF = 1792;
constexpr int NCLUSTER = 66, NCTA = 132;
constexpr int NSLOT = 5;
constexpr uint32_t SLOT_BYTES = 32768;
constexpr uint32_t QB_OFF = NSLOT * SLOT_BYTES;
constexpr uint32_t BAR_OFF = QB_OFF + 65536;
constexpr uint32_t SFULL_OFF = BAR_OFF + 128, SFREE_OFF = BAR_OFF + 160;
constexpr uint32_t SMEM_BYTES = BAR_OFF + 256 + 1024;
constexpr int MAXITEMS = 12;

enum { IT_END = 0, IT_KV = 1, IT_GU = 2, IT_DN = 3, IT_AT = 4 };

constexpr int CNT_DONE = 0;
constexpr int CNT_LN = 32;
constexpr int CNT_GU = 64;
constexpr int CNT_DN = 96;
constexpr int CNT_P = 128;
constexpr int CNT_CTX = 384;
constexpr int CNT_KV = 640;
constexpr int CNT_TOTAL = 640 + 512;

__device__ __align__(1024) bf16 g_xn[SEQ * DM];
__device__ __align__(1024) bf16 g_kv[SEQ * 2 * NH * HD];
__device__ __align__(1024) bf16 g_h[SEQ * FF];
__device__ __align__(1024) bf16 g_sg[SEQ * DM];
__device__ __align__(1024) bf16 g_part[(NH / 2) * SEQ * DM];
__device__ __align__(1024) uint4 g_ctx[8 * 32 * 16 * 128];
__device__ __align__(128) unsigned g_cnt[CNT_TOTAL];

struct Params {
    CUtensorMap ckv, wuk, wuv, xn, wg, wu, wd, wq, wo, k_ld, v_ld, h, sg_st, p_st, p_ld, x_ld, g_ld;
    const bf16 *x, *pwq, *pwuk, *pwuv;
    bf16* out;
    uint16_t sched[NCLUSTER][MAXITEMS];
};

__device__ __forceinline__ uint32_t smem_u32(const void* p) { return (uint32_t)__cvta_generic_to_shared(p); }
__device__ __forceinline__ void mbar_init(uint32_t bar, uint32_t count) {
    asm volatile("mbarrier.init.shared::cta.b64 [%0], %1;" ::"r"(bar), "r"(count) : "memory");
}
__device__ __forceinline__ void mbar_expect_tx(uint32_t bar, uint32_t bytes) {
    asm volatile("mbarrier.arrive.expect_tx.shared::cta.b64 _, [%0], %1;" ::"r"(bar), "r"(bytes) : "memory");
}
__device__ __forceinline__ void mbar_arrive_cluster(uint32_t cluster_addr) {
    asm volatile("mbarrier.arrive.shared::cluster.b64 _, [%0];" ::"r"(cluster_addr) : "memory");
}
__device__ __forceinline__ uint32_t mapa(uint32_t addr, uint32_t cta) {
    uint32_t r;
    asm volatile("mapa.shared::cluster.u32 %0, %1, %2;" : "=r"(r) : "r"(addr), "r"(cta));
    return r;
}
__device__ __forceinline__ bool mbar_try(uint32_t bar, uint32_t parity) {
    uint32_t ok;
    asm volatile("{\n.reg .pred p;\nmbarrier.try_wait.parity.shared::cta.b64 p, [%1], %2;\nselp.u32 %0, 1, 0, p;\n}"
                 : "=r"(ok) : "r"(bar), "r"(parity) : "memory");
    return ok != 0;
}
__device__ __forceinline__ void trap_if(bool c) {
    asm volatile("{\n.reg .pred p;\nsetp.ne.u32 p, %0, 0;\n@p trap;\n}" ::"r"((uint32_t)c));
}
__device__ __forceinline__ void mbar_wait(uint32_t bar, uint32_t parity) {
    while (!mbar_try(bar, parity)) {}
}
__device__ __forceinline__ void tma_load_3d(uint32_t dst, const CUtensorMap* map, uint32_t bar, int c0, int c1, int c2) {
    asm volatile("cp.async.bulk.tensor.3d.shared::cluster.global.mbarrier::complete_tx::bytes [%0], [%1, {%3, %4, %5}], [%2];"
                 ::"r"(dst), "l"((uint64_t)map), "r"(bar), "r"(c0), "r"(c1), "r"(c2) : "memory");
}
__device__ __forceinline__ void tma_load_3d_mc(uint32_t dst, const CUtensorMap* map, uint32_t bar, int c0, int c1, int c2) {
    asm volatile("cp.async.bulk.tensor.3d.shared::cluster.global.mbarrier::complete_tx::bytes.multicast::cluster [%0], [%1, {%3, %4, %5}], [%2], %6;"
                 ::"r"(dst), "l"((uint64_t)map), "r"(bar), "r"(c0), "r"(c1), "r"(c2), "h"((uint16_t)3) : "memory");
}
__device__ __forceinline__ void tma_store_3d(const CUtensorMap* map, uint32_t src, int c0, int c1, int c2) {
    asm volatile("cp.async.bulk.tensor.3d.global.shared::cta.bulk_group [%0, {%2, %3, %4}], [%1];"
                 ::"l"((uint64_t)map), "r"(src), "r"(c0), "r"(c1), "r"(c2) : "memory");
}
__device__ __forceinline__ void bulk_commit() { asm volatile("cp.async.bulk.commit_group;" ::: "memory"); }
template <int N> __device__ __forceinline__ void bulk_wait_read() { asm volatile("cp.async.bulk.wait_group.read %0;" ::"n"(N) : "memory"); }
template <int N> __device__ __forceinline__ void bulk_wait() { asm volatile("cp.async.bulk.wait_group %0;" ::"n"(N) : "memory"); }
__device__ __forceinline__ void fence_async_smem() { asm volatile("fence.proxy.async.shared::cta;" ::: "memory"); }
__device__ __forceinline__ void fence_async_all() { asm volatile("fence.proxy.async;" ::: "memory"); }
__device__ __forceinline__ void cluster_sync_relaxed() {
    asm volatile("barrier.cluster.arrive.relaxed.aligned;\nbarrier.cluster.wait.aligned;" ::: "memory");
}
__device__ __forceinline__ void bar_sync(int id, int n) { asm volatile("bar.sync %0, %1;" ::"r"(id), "r"(n) : "memory"); }
__device__ __forceinline__ void bar_arrive(int id, int n) { asm volatile("bar.arrive %0, %1;" ::"r"(id), "r"(n) : "memory"); }
__device__ __forceinline__ void wg_fence() { asm volatile("wgmma.fence.sync.aligned;" ::: "memory"); }
__device__ __forceinline__ void wg_commit() { asm volatile("wgmma.commit_group.sync.aligned;" ::: "memory"); }
template <int N> __device__ __forceinline__ void wg_wait() { asm volatile("wgmma.wait_group.sync.aligned %0;" ::"n"(N) : "memory"); }
__device__ __forceinline__ unsigned ld_acquire(const unsigned* p) {
    unsigned v;
    asm volatile("ld.acquire.gpu.global.u32 %0, [%1];" : "=r"(v) : "l"(p) : "memory");
    return v;
}
__device__ __forceinline__ void red_release(unsigned* p, unsigned v) {
    asm volatile("red.release.gpu.global.add.u32 [%0], %1;" ::"l"(p), "r"(v) : "memory");
}
__device__ __forceinline__ void red_relaxed(unsigned* p) {
    asm volatile("red.relaxed.gpu.global.add.u32 [%0], 1;" ::"l"(p) : "memory");
}
__device__ __forceinline__ int fresh_tid() {
    int t;
    asm volatile("mov.u32 %0, %%tid.x;" : "=r"(t));
    return t;
}
__device__ __forceinline__ float ex2(float x) {
    float y;
    asm("ex2.approx.ftz.f32 %0, %1;" : "=f"(y) : "f"(x));
    return y;
}
__device__ __forceinline__ uint32_t pack_bf16(float lo, float hi) {
    uint32_t r;
    asm("cvt.rn.bf16x2.f32 %0, %1, %2;" : "=r"(r) : "f"(hi), "f"(lo));
    return r;
}
__device__ __forceinline__ float bf16r(float x) { return __bfloat162float(__float2bfloat16_rn(x)); }
__device__ __forceinline__ float bf_lo(uint32_t v) { return __uint_as_float(v << 16); }
__device__ __forceinline__ float bf_hi(uint32_t v) { return __uint_as_float(v & 0xffff0000u); }
__device__ __forceinline__ void stsm4(uint32_t addr, uint32_t r0, uint32_t r1, uint32_t r2, uint32_t r3) {
    asm volatile("stmatrix.sync.aligned.m8n8.x4.shared.b16 [%0], {%1, %2, %3, %4};" ::"r"(addr), "r"(r0), "r"(r1), "r"(r2), "r"(r3) : "memory");
}
__device__ __forceinline__ uint32_t make_desc(uint32_t addr, uint32_t lbo, uint32_t  ) {
    return ((addr & 0x3FFFF) >> 4) | ((lbo >> 4) << 16);
}
__device__ __forceinline__ float rcp(float x) {
    float y;
    asm("rcp.approx.ftz.f32 %0, %1;" : "=f"(y) : "f"(x));
    return y;
}
__device__ __forceinline__ float tanh_hw(float x) {
    float y;
    asm("tanh.approx.f32 %0, %1;" : "=f"(y) : "f"(x));
    return y;
}
__device__ __forceinline__ float sqrt_approx(float x) {
    float y;
    asm("sqrt.approx.f32 %0, %1;" : "=f"(y) : "f"(x));
    return y;
}
__device__ __forceinline__ void silu2(float g0, float g1, float& s0, float& s1) {
    const float d0 = 1.0f + ex2(fminf(-1.4426950408889634f * g0, 60.0f));
    const float d1 = 1.0f + ex2(fminf(-1.4426950408889634f * g1, 60.0f));
    const float r = rcp(d0 * d1);
    s0 = g0 * (r * d1);
    s1 = g1 * (r * d0);
}
__device__ __forceinline__ void bf16r2(float& a, float& b) {
    const uint32_t p = pack_bf16(a, b);
    a = bf_lo(p); b = bf_hi(p);
}

template <int OFF = 0> __device__ __forceinline__ void wgmma_n256_ss_tb1(float (&d)[128], uint32_t descA, uint32_t descB) {
    asm volatile("{\n.reg .pred p;\n.reg .b32 hi;\n.reg .b64 da, db;\nsetp.ne.b32 p, 1, 0;\nmov.b32 hi, 0x40000040;\nmov.b64 da, {%128, hi};\nmov.b64 db, {%129, hi};\n"
        "wgmma.mma_async.sync.aligned.m64n256k16.f32.bf16.bf16 {%0, %1, %2, %3, %4, %5, %6, %7, %8, %9, %10, %11, %12, %13, %14, %15, %16, %17, %18, %19, %20, %21, %22, %23, %24, %25, %26, %27, %28, %29, %30, %31, %32, %33, %34, %35, %36, %37, %38, %39, %40, %41, %42, %43, %44, %45, %46, %47, %48, %49, %50, %51, %52, %53, %54, %55, %56, %57, %58, %59, %60, %61, %62, %63, %64, %65, %66, %67, %68, %69, %70, %71, %72, %73, %74, %75, %76, %77, %78, %79, %80, %81, %82, %83, %84, %85, %86, %87, %88, %89, %90, %91, %92, %93, %94, %95, %96, %97, %98, %99, %100, %101, %102, %103, %104, %105, %106, %107, %108, %109, %110, %111, %112, %113, %114, %115, %116, %117, %118, %119, %120, %121, %122, %123, %124, %125, %126, %127}, da, db, p, 1, 1, 0, 1;\n}\n"
        : "+f"(d[OFF + 0]), "+f"(d[OFF + 1]), "+f"(d[OFF + 2]), "+f"(d[OFF + 3]), "+f"(d[OFF + 4]), "+f"(d[OFF + 5]), "+f"(d[OFF + 6]), "+f"(d[OFF + 7]),
          "+f"(d[OFF + 8]), "+f"(d[OFF + 9]), "+f"(d[OFF + 10]), "+f"(d[OFF + 11]), "+f"(d[OFF + 12]), "+f"(d[OFF + 13]), "+f"(d[OFF + 14]), "+f"(d[OFF + 15]),
          "+f"(d[OFF + 16]), "+f"(d[OFF + 17]), "+f"(d[OFF + 18]), "+f"(d[OFF + 19]), "+f"(d[OFF + 20]), "+f"(d[OFF + 21]), "+f"(d[OFF + 22]), "+f"(d[OFF + 23]),
          "+f"(d[OFF + 24]), "+f"(d[OFF + 25]), "+f"(d[OFF + 26]), "+f"(d[OFF + 27]), "+f"(d[OFF + 28]), "+f"(d[OFF + 29]), "+f"(d[OFF + 30]), "+f"(d[OFF + 31]),
          "+f"(d[OFF + 32]), "+f"(d[OFF + 33]), "+f"(d[OFF + 34]), "+f"(d[OFF + 35]), "+f"(d[OFF + 36]), "+f"(d[OFF + 37]), "+f"(d[OFF + 38]), "+f"(d[OFF + 39]),
          "+f"(d[OFF + 40]), "+f"(d[OFF + 41]), "+f"(d[OFF + 42]), "+f"(d[OFF + 43]), "+f"(d[OFF + 44]), "+f"(d[OFF + 45]), "+f"(d[OFF + 46]), "+f"(d[OFF + 47]),
          "+f"(d[OFF + 48]), "+f"(d[OFF + 49]), "+f"(d[OFF + 50]), "+f"(d[OFF + 51]), "+f"(d[OFF + 52]), "+f"(d[OFF + 53]), "+f"(d[OFF + 54]), "+f"(d[OFF + 55]),
          "+f"(d[OFF + 56]), "+f"(d[OFF + 57]), "+f"(d[OFF + 58]), "+f"(d[OFF + 59]), "+f"(d[OFF + 60]), "+f"(d[OFF + 61]), "+f"(d[OFF + 62]), "+f"(d[OFF + 63]),
          "+f"(d[OFF + 64]), "+f"(d[OFF + 65]), "+f"(d[OFF + 66]), "+f"(d[OFF + 67]), "+f"(d[OFF + 68]), "+f"(d[OFF + 69]), "+f"(d[OFF + 70]), "+f"(d[OFF + 71]),
          "+f"(d[OFF + 72]), "+f"(d[OFF + 73]), "+f"(d[OFF + 74]), "+f"(d[OFF + 75]), "+f"(d[OFF + 76]), "+f"(d[OFF + 77]), "+f"(d[OFF + 78]), "+f"(d[OFF + 79]),
          "+f"(d[OFF + 80]), "+f"(d[OFF + 81]), "+f"(d[OFF + 82]), "+f"(d[OFF + 83]), "+f"(d[OFF + 84]), "+f"(d[OFF + 85]), "+f"(d[OFF + 86]), "+f"(d[OFF + 87]),
          "+f"(d[OFF + 88]), "+f"(d[OFF + 89]), "+f"(d[OFF + 90]), "+f"(d[OFF + 91]), "+f"(d[OFF + 92]), "+f"(d[OFF + 93]), "+f"(d[OFF + 94]), "+f"(d[OFF + 95]),
          "+f"(d[OFF + 96]), "+f"(d[OFF + 97]), "+f"(d[OFF + 98]), "+f"(d[OFF + 99]), "+f"(d[OFF + 100]), "+f"(d[OFF + 101]), "+f"(d[OFF + 102]), "+f"(d[OFF + 103]),
          "+f"(d[OFF + 104]), "+f"(d[OFF + 105]), "+f"(d[OFF + 106]), "+f"(d[OFF + 107]), "+f"(d[OFF + 108]), "+f"(d[OFF + 109]), "+f"(d[OFF + 110]), "+f"(d[OFF + 111]),
          "+f"(d[OFF + 112]), "+f"(d[OFF + 113]), "+f"(d[OFF + 114]), "+f"(d[OFF + 115]), "+f"(d[OFF + 116]), "+f"(d[OFF + 117]), "+f"(d[OFF + 118]), "+f"(d[OFF + 119]),
          "+f"(d[OFF + 120]), "+f"(d[OFF + 121]), "+f"(d[OFF + 122]), "+f"(d[OFF + 123]), "+f"(d[OFF + 124]), "+f"(d[OFF + 125]), "+f"(d[OFF + 126]), "+f"(d[OFF + 127])
        : "r"(descA), "r"(descB));
}

template <int OFF = 0> __device__ __forceinline__ void wgmma_n256_ss_tb1_z(float (&d)[128], uint32_t descA, uint32_t descB) {
    asm volatile("{\n.reg .pred p;\n.reg .b32 hi;\n.reg .b64 da, db;\nsetp.ne.b32 p, 0, 0;\nmov.b32 hi, 0x40000040;\nmov.b64 da, {%128, hi};\nmov.b64 db, {%129, hi};\n"
        "wgmma.mma_async.sync.aligned.m64n256k16.f32.bf16.bf16 {%0, %1, %2, %3, %4, %5, %6, %7, %8, %9, %10, %11, %12, %13, %14, %15, %16, %17, %18, %19, %20, %21, %22, %23, %24, %25, %26, %27, %28, %29, %30, %31, %32, %33, %34, %35, %36, %37, %38, %39, %40, %41, %42, %43, %44, %45, %46, %47, %48, %49, %50, %51, %52, %53, %54, %55, %56, %57, %58, %59, %60, %61, %62, %63, %64, %65, %66, %67, %68, %69, %70, %71, %72, %73, %74, %75, %76, %77, %78, %79, %80, %81, %82, %83, %84, %85, %86, %87, %88, %89, %90, %91, %92, %93, %94, %95, %96, %97, %98, %99, %100, %101, %102, %103, %104, %105, %106, %107, %108, %109, %110, %111, %112, %113, %114, %115, %116, %117, %118, %119, %120, %121, %122, %123, %124, %125, %126, %127}, da, db, p, 1, 1, 0, 1;\n}\n"
        : "=f"(d[OFF + 0]), "=f"(d[OFF + 1]), "=f"(d[OFF + 2]), "=f"(d[OFF + 3]), "=f"(d[OFF + 4]), "=f"(d[OFF + 5]), "=f"(d[OFF + 6]), "=f"(d[OFF + 7]),
          "=f"(d[OFF + 8]), "=f"(d[OFF + 9]), "=f"(d[OFF + 10]), "=f"(d[OFF + 11]), "=f"(d[OFF + 12]), "=f"(d[OFF + 13]), "=f"(d[OFF + 14]), "=f"(d[OFF + 15]),
          "=f"(d[OFF + 16]), "=f"(d[OFF + 17]), "=f"(d[OFF + 18]), "=f"(d[OFF + 19]), "=f"(d[OFF + 20]), "=f"(d[OFF + 21]), "=f"(d[OFF + 22]), "=f"(d[OFF + 23]),
          "=f"(d[OFF + 24]), "=f"(d[OFF + 25]), "=f"(d[OFF + 26]), "=f"(d[OFF + 27]), "=f"(d[OFF + 28]), "=f"(d[OFF + 29]), "=f"(d[OFF + 30]), "=f"(d[OFF + 31]),
          "=f"(d[OFF + 32]), "=f"(d[OFF + 33]), "=f"(d[OFF + 34]), "=f"(d[OFF + 35]), "=f"(d[OFF + 36]), "=f"(d[OFF + 37]), "=f"(d[OFF + 38]), "=f"(d[OFF + 39]),
          "=f"(d[OFF + 40]), "=f"(d[OFF + 41]), "=f"(d[OFF + 42]), "=f"(d[OFF + 43]), "=f"(d[OFF + 44]), "=f"(d[OFF + 45]), "=f"(d[OFF + 46]), "=f"(d[OFF + 47]),
          "=f"(d[OFF + 48]), "=f"(d[OFF + 49]), "=f"(d[OFF + 50]), "=f"(d[OFF + 51]), "=f"(d[OFF + 52]), "=f"(d[OFF + 53]), "=f"(d[OFF + 54]), "=f"(d[OFF + 55]),
          "=f"(d[OFF + 56]), "=f"(d[OFF + 57]), "=f"(d[OFF + 58]), "=f"(d[OFF + 59]), "=f"(d[OFF + 60]), "=f"(d[OFF + 61]), "=f"(d[OFF + 62]), "=f"(d[OFF + 63]),
          "=f"(d[OFF + 64]), "=f"(d[OFF + 65]), "=f"(d[OFF + 66]), "=f"(d[OFF + 67]), "=f"(d[OFF + 68]), "=f"(d[OFF + 69]), "=f"(d[OFF + 70]), "=f"(d[OFF + 71]),
          "=f"(d[OFF + 72]), "=f"(d[OFF + 73]), "=f"(d[OFF + 74]), "=f"(d[OFF + 75]), "=f"(d[OFF + 76]), "=f"(d[OFF + 77]), "=f"(d[OFF + 78]), "=f"(d[OFF + 79]),
          "=f"(d[OFF + 80]), "=f"(d[OFF + 81]), "=f"(d[OFF + 82]), "=f"(d[OFF + 83]), "=f"(d[OFF + 84]), "=f"(d[OFF + 85]), "=f"(d[OFF + 86]), "=f"(d[OFF + 87]),
          "=f"(d[OFF + 88]), "=f"(d[OFF + 89]), "=f"(d[OFF + 90]), "=f"(d[OFF + 91]), "=f"(d[OFF + 92]), "=f"(d[OFF + 93]), "=f"(d[OFF + 94]), "=f"(d[OFF + 95]),
          "=f"(d[OFF + 96]), "=f"(d[OFF + 97]), "=f"(d[OFF + 98]), "=f"(d[OFF + 99]), "=f"(d[OFF + 100]), "=f"(d[OFF + 101]), "=f"(d[OFF + 102]), "=f"(d[OFF + 103]),
          "=f"(d[OFF + 104]), "=f"(d[OFF + 105]), "=f"(d[OFF + 106]), "=f"(d[OFF + 107]), "=f"(d[OFF + 108]), "=f"(d[OFF + 109]), "=f"(d[OFF + 110]), "=f"(d[OFF + 111]),
          "=f"(d[OFF + 112]), "=f"(d[OFF + 113]), "=f"(d[OFF + 114]), "=f"(d[OFF + 115]), "=f"(d[OFF + 116]), "=f"(d[OFF + 117]), "=f"(d[OFF + 118]), "=f"(d[OFF + 119]),
          "=f"(d[OFF + 120]), "=f"(d[OFF + 121]), "=f"(d[OFF + 122]), "=f"(d[OFF + 123]), "=f"(d[OFF + 124]), "=f"(d[OFF + 125]), "=f"(d[OFF + 126]), "=f"(d[OFF + 127])
        : "r"(descA), "r"(descB));
}

template <int OFF = 0> __device__ __forceinline__ void wgmma_n192_ss_tb1(float (&d)[128], uint32_t descA, uint32_t descB) {
    asm volatile("{\n.reg .pred p;\n.reg .b32 hi;\n.reg .b64 da, db;\nsetp.ne.b32 p, 1, 0;\nmov.b32 hi, 0x40000040;\nmov.b64 da, {%96, hi};\nmov.b64 db, {%97, hi};\n"
        "wgmma.mma_async.sync.aligned.m64n192k16.f32.bf16.bf16 {%0, %1, %2, %3, %4, %5, %6, %7, %8, %9, %10, %11, %12, %13, %14, %15, %16, %17, %18, %19, %20, %21, %22, %23, %24, %25, %26, %27, %28, %29, %30, %31, %32, %33, %34, %35, %36, %37, %38, %39, %40, %41, %42, %43, %44, %45, %46, %47, %48, %49, %50, %51, %52, %53, %54, %55, %56, %57, %58, %59, %60, %61, %62, %63, %64, %65, %66, %67, %68, %69, %70, %71, %72, %73, %74, %75, %76, %77, %78, %79, %80, %81, %82, %83, %84, %85, %86, %87, %88, %89, %90, %91, %92, %93, %94, %95}, da, db, p, 1, 1, 0, 1;\n}\n"
        : "+f"(d[OFF + 0]), "+f"(d[OFF + 1]), "+f"(d[OFF + 2]), "+f"(d[OFF + 3]), "+f"(d[OFF + 4]), "+f"(d[OFF + 5]), "+f"(d[OFF + 6]), "+f"(d[OFF + 7]),
          "+f"(d[OFF + 8]), "+f"(d[OFF + 9]), "+f"(d[OFF + 10]), "+f"(d[OFF + 11]), "+f"(d[OFF + 12]), "+f"(d[OFF + 13]), "+f"(d[OFF + 14]), "+f"(d[OFF + 15]),
          "+f"(d[OFF + 16]), "+f"(d[OFF + 17]), "+f"(d[OFF + 18]), "+f"(d[OFF + 19]), "+f"(d[OFF + 20]), "+f"(d[OFF + 21]), "+f"(d[OFF + 22]), "+f"(d[OFF + 23]),
          "+f"(d[OFF + 24]), "+f"(d[OFF + 25]), "+f"(d[OFF + 26]), "+f"(d[OFF + 27]), "+f"(d[OFF + 28]), "+f"(d[OFF + 29]), "+f"(d[OFF + 30]), "+f"(d[OFF + 31]),
          "+f"(d[OFF + 32]), "+f"(d[OFF + 33]), "+f"(d[OFF + 34]), "+f"(d[OFF + 35]), "+f"(d[OFF + 36]), "+f"(d[OFF + 37]), "+f"(d[OFF + 38]), "+f"(d[OFF + 39]),
          "+f"(d[OFF + 40]), "+f"(d[OFF + 41]), "+f"(d[OFF + 42]), "+f"(d[OFF + 43]), "+f"(d[OFF + 44]), "+f"(d[OFF + 45]), "+f"(d[OFF + 46]), "+f"(d[OFF + 47]),
          "+f"(d[OFF + 48]), "+f"(d[OFF + 49]), "+f"(d[OFF + 50]), "+f"(d[OFF + 51]), "+f"(d[OFF + 52]), "+f"(d[OFF + 53]), "+f"(d[OFF + 54]), "+f"(d[OFF + 55]),
          "+f"(d[OFF + 56]), "+f"(d[OFF + 57]), "+f"(d[OFF + 58]), "+f"(d[OFF + 59]), "+f"(d[OFF + 60]), "+f"(d[OFF + 61]), "+f"(d[OFF + 62]), "+f"(d[OFF + 63]),
          "+f"(d[OFF + 64]), "+f"(d[OFF + 65]), "+f"(d[OFF + 66]), "+f"(d[OFF + 67]), "+f"(d[OFF + 68]), "+f"(d[OFF + 69]), "+f"(d[OFF + 70]), "+f"(d[OFF + 71]),
          "+f"(d[OFF + 72]), "+f"(d[OFF + 73]), "+f"(d[OFF + 74]), "+f"(d[OFF + 75]), "+f"(d[OFF + 76]), "+f"(d[OFF + 77]), "+f"(d[OFF + 78]), "+f"(d[OFF + 79]),
          "+f"(d[OFF + 80]), "+f"(d[OFF + 81]), "+f"(d[OFF + 82]), "+f"(d[OFF + 83]), "+f"(d[OFF + 84]), "+f"(d[OFF + 85]), "+f"(d[OFF + 86]), "+f"(d[OFF + 87]),
          "+f"(d[OFF + 88]), "+f"(d[OFF + 89]), "+f"(d[OFF + 90]), "+f"(d[OFF + 91]), "+f"(d[OFF + 92]), "+f"(d[OFF + 93]), "+f"(d[OFF + 94]), "+f"(d[OFF + 95])
        : "r"(descA), "r"(descB));
}

template <int OFF = 0> __device__ __forceinline__ void wgmma_n192_ss_tb1_z(float (&d)[128], uint32_t descA, uint32_t descB) {
    asm volatile("{\n.reg .pred p;\n.reg .b32 hi;\n.reg .b64 da, db;\nsetp.ne.b32 p, 0, 0;\nmov.b32 hi, 0x40000040;\nmov.b64 da, {%96, hi};\nmov.b64 db, {%97, hi};\n"
        "wgmma.mma_async.sync.aligned.m64n192k16.f32.bf16.bf16 {%0, %1, %2, %3, %4, %5, %6, %7, %8, %9, %10, %11, %12, %13, %14, %15, %16, %17, %18, %19, %20, %21, %22, %23, %24, %25, %26, %27, %28, %29, %30, %31, %32, %33, %34, %35, %36, %37, %38, %39, %40, %41, %42, %43, %44, %45, %46, %47, %48, %49, %50, %51, %52, %53, %54, %55, %56, %57, %58, %59, %60, %61, %62, %63, %64, %65, %66, %67, %68, %69, %70, %71, %72, %73, %74, %75, %76, %77, %78, %79, %80, %81, %82, %83, %84, %85, %86, %87, %88, %89, %90, %91, %92, %93, %94, %95}, da, db, p, 1, 1, 0, 1;\n}\n"
        : "=f"(d[OFF + 0]), "=f"(d[OFF + 1]), "=f"(d[OFF + 2]), "=f"(d[OFF + 3]), "=f"(d[OFF + 4]), "=f"(d[OFF + 5]), "=f"(d[OFF + 6]), "=f"(d[OFF + 7]),
          "=f"(d[OFF + 8]), "=f"(d[OFF + 9]), "=f"(d[OFF + 10]), "=f"(d[OFF + 11]), "=f"(d[OFF + 12]), "=f"(d[OFF + 13]), "=f"(d[OFF + 14]), "=f"(d[OFF + 15]),
          "=f"(d[OFF + 16]), "=f"(d[OFF + 17]), "=f"(d[OFF + 18]), "=f"(d[OFF + 19]), "=f"(d[OFF + 20]), "=f"(d[OFF + 21]), "=f"(d[OFF + 22]), "=f"(d[OFF + 23]),
          "=f"(d[OFF + 24]), "=f"(d[OFF + 25]), "=f"(d[OFF + 26]), "=f"(d[OFF + 27]), "=f"(d[OFF + 28]), "=f"(d[OFF + 29]), "=f"(d[OFF + 30]), "=f"(d[OFF + 31]),
          "=f"(d[OFF + 32]), "=f"(d[OFF + 33]), "=f"(d[OFF + 34]), "=f"(d[OFF + 35]), "=f"(d[OFF + 36]), "=f"(d[OFF + 37]), "=f"(d[OFF + 38]), "=f"(d[OFF + 39]),
          "=f"(d[OFF + 40]), "=f"(d[OFF + 41]), "=f"(d[OFF + 42]), "=f"(d[OFF + 43]), "=f"(d[OFF + 44]), "=f"(d[OFF + 45]), "=f"(d[OFF + 46]), "=f"(d[OFF + 47]),
          "=f"(d[OFF + 48]), "=f"(d[OFF + 49]), "=f"(d[OFF + 50]), "=f"(d[OFF + 51]), "=f"(d[OFF + 52]), "=f"(d[OFF + 53]), "=f"(d[OFF + 54]), "=f"(d[OFF + 55]),
          "=f"(d[OFF + 56]), "=f"(d[OFF + 57]), "=f"(d[OFF + 58]), "=f"(d[OFF + 59]), "=f"(d[OFF + 60]), "=f"(d[OFF + 61]), "=f"(d[OFF + 62]), "=f"(d[OFF + 63]),
          "=f"(d[OFF + 64]), "=f"(d[OFF + 65]), "=f"(d[OFF + 66]), "=f"(d[OFF + 67]), "=f"(d[OFF + 68]), "=f"(d[OFF + 69]), "=f"(d[OFF + 70]), "=f"(d[OFF + 71]),
          "=f"(d[OFF + 72]), "=f"(d[OFF + 73]), "=f"(d[OFF + 74]), "=f"(d[OFF + 75]), "=f"(d[OFF + 76]), "=f"(d[OFF + 77]), "=f"(d[OFF + 78]), "=f"(d[OFF + 79]),
          "=f"(d[OFF + 80]), "=f"(d[OFF + 81]), "=f"(d[OFF + 82]), "=f"(d[OFF + 83]), "=f"(d[OFF + 84]), "=f"(d[OFF + 85]), "=f"(d[OFF + 86]), "=f"(d[OFF + 87]),
          "=f"(d[OFF + 88]), "=f"(d[OFF + 89]), "=f"(d[OFF + 90]), "=f"(d[OFF + 91]), "=f"(d[OFF + 92]), "=f"(d[OFF + 93]), "=f"(d[OFF + 94]), "=f"(d[OFF + 95])
        : "r"(descA), "r"(descB));
}

template <int OFF = 0> __device__ __forceinline__ void wgmma_n128_ss_tb0(float (&d)[64], uint32_t descA, uint32_t descB) {
    asm volatile("{\n.reg .pred p;\n.reg .b32 hi;\n.reg .b64 da, db;\nsetp.ne.b32 p, 1, 0;\nmov.b32 hi, 0x40000040;\nmov.b64 da, {%64, hi};\nmov.b64 db, {%65, hi};\n"
        "wgmma.mma_async.sync.aligned.m64n128k16.f32.bf16.bf16 {%0, %1, %2, %3, %4, %5, %6, %7, %8, %9, %10, %11, %12, %13, %14, %15, %16, %17, %18, %19, %20, %21, %22, %23, %24, %25, %26, %27, %28, %29, %30, %31, %32, %33, %34, %35, %36, %37, %38, %39, %40, %41, %42, %43, %44, %45, %46, %47, %48, %49, %50, %51, %52, %53, %54, %55, %56, %57, %58, %59, %60, %61, %62, %63}, da, db, p, 1, 1, 0, 0;\n}\n"
        : "+f"(d[OFF + 0]), "+f"(d[OFF + 1]), "+f"(d[OFF + 2]), "+f"(d[OFF + 3]), "+f"(d[OFF + 4]), "+f"(d[OFF + 5]), "+f"(d[OFF + 6]), "+f"(d[OFF + 7]),
          "+f"(d[OFF + 8]), "+f"(d[OFF + 9]), "+f"(d[OFF + 10]), "+f"(d[OFF + 11]), "+f"(d[OFF + 12]), "+f"(d[OFF + 13]), "+f"(d[OFF + 14]), "+f"(d[OFF + 15]),
          "+f"(d[OFF + 16]), "+f"(d[OFF + 17]), "+f"(d[OFF + 18]), "+f"(d[OFF + 19]), "+f"(d[OFF + 20]), "+f"(d[OFF + 21]), "+f"(d[OFF + 22]), "+f"(d[OFF + 23]),
          "+f"(d[OFF + 24]), "+f"(d[OFF + 25]), "+f"(d[OFF + 26]), "+f"(d[OFF + 27]), "+f"(d[OFF + 28]), "+f"(d[OFF + 29]), "+f"(d[OFF + 30]), "+f"(d[OFF + 31]),
          "+f"(d[OFF + 32]), "+f"(d[OFF + 33]), "+f"(d[OFF + 34]), "+f"(d[OFF + 35]), "+f"(d[OFF + 36]), "+f"(d[OFF + 37]), "+f"(d[OFF + 38]), "+f"(d[OFF + 39]),
          "+f"(d[OFF + 40]), "+f"(d[OFF + 41]), "+f"(d[OFF + 42]), "+f"(d[OFF + 43]), "+f"(d[OFF + 44]), "+f"(d[OFF + 45]), "+f"(d[OFF + 46]), "+f"(d[OFF + 47]),
          "+f"(d[OFF + 48]), "+f"(d[OFF + 49]), "+f"(d[OFF + 50]), "+f"(d[OFF + 51]), "+f"(d[OFF + 52]), "+f"(d[OFF + 53]), "+f"(d[OFF + 54]), "+f"(d[OFF + 55]),
          "+f"(d[OFF + 56]), "+f"(d[OFF + 57]), "+f"(d[OFF + 58]), "+f"(d[OFF + 59]), "+f"(d[OFF + 60]), "+f"(d[OFF + 61]), "+f"(d[OFF + 62]), "+f"(d[OFF + 63])
        : "r"(descA), "r"(descB));
}

template <int OFF = 0> __device__ __forceinline__ void wgmma_n128_ss_tb0_z(float (&d)[64], uint32_t descA, uint32_t descB) {
    asm volatile("{\n.reg .pred p;\n.reg .b32 hi;\n.reg .b64 da, db;\nsetp.ne.b32 p, 0, 0;\nmov.b32 hi, 0x40000040;\nmov.b64 da, {%64, hi};\nmov.b64 db, {%65, hi};\n"
        "wgmma.mma_async.sync.aligned.m64n128k16.f32.bf16.bf16 {%0, %1, %2, %3, %4, %5, %6, %7, %8, %9, %10, %11, %12, %13, %14, %15, %16, %17, %18, %19, %20, %21, %22, %23, %24, %25, %26, %27, %28, %29, %30, %31, %32, %33, %34, %35, %36, %37, %38, %39, %40, %41, %42, %43, %44, %45, %46, %47, %48, %49, %50, %51, %52, %53, %54, %55, %56, %57, %58, %59, %60, %61, %62, %63}, da, db, p, 1, 1, 0, 0;\n}\n"
        : "=f"(d[OFF + 0]), "=f"(d[OFF + 1]), "=f"(d[OFF + 2]), "=f"(d[OFF + 3]), "=f"(d[OFF + 4]), "=f"(d[OFF + 5]), "=f"(d[OFF + 6]), "=f"(d[OFF + 7]),
          "=f"(d[OFF + 8]), "=f"(d[OFF + 9]), "=f"(d[OFF + 10]), "=f"(d[OFF + 11]), "=f"(d[OFF + 12]), "=f"(d[OFF + 13]), "=f"(d[OFF + 14]), "=f"(d[OFF + 15]),
          "=f"(d[OFF + 16]), "=f"(d[OFF + 17]), "=f"(d[OFF + 18]), "=f"(d[OFF + 19]), "=f"(d[OFF + 20]), "=f"(d[OFF + 21]), "=f"(d[OFF + 22]), "=f"(d[OFF + 23]),
          "=f"(d[OFF + 24]), "=f"(d[OFF + 25]), "=f"(d[OFF + 26]), "=f"(d[OFF + 27]), "=f"(d[OFF + 28]), "=f"(d[OFF + 29]), "=f"(d[OFF + 30]), "=f"(d[OFF + 31]),
          "=f"(d[OFF + 32]), "=f"(d[OFF + 33]), "=f"(d[OFF + 34]), "=f"(d[OFF + 35]), "=f"(d[OFF + 36]), "=f"(d[OFF + 37]), "=f"(d[OFF + 38]), "=f"(d[OFF + 39]),
          "=f"(d[OFF + 40]), "=f"(d[OFF + 41]), "=f"(d[OFF + 42]), "=f"(d[OFF + 43]), "=f"(d[OFF + 44]), "=f"(d[OFF + 45]), "=f"(d[OFF + 46]), "=f"(d[OFF + 47]),
          "=f"(d[OFF + 48]), "=f"(d[OFF + 49]), "=f"(d[OFF + 50]), "=f"(d[OFF + 51]), "=f"(d[OFF + 52]), "=f"(d[OFF + 53]), "=f"(d[OFF + 54]), "=f"(d[OFF + 55]),
          "=f"(d[OFF + 56]), "=f"(d[OFF + 57]), "=f"(d[OFF + 58]), "=f"(d[OFF + 59]), "=f"(d[OFF + 60]), "=f"(d[OFF + 61]), "=f"(d[OFF + 62]), "=f"(d[OFF + 63])
        : "r"(descA), "r"(descB));
}

template <int OFF = 0> __device__ __forceinline__ void wgmma_n64_ss_tb0(float (&d)[64], uint32_t descA, uint32_t descB) {
    asm volatile("{\n.reg .pred p;\n.reg .b32 hi;\n.reg .b64 da, db;\nsetp.ne.b32 p, 1, 0;\nmov.b32 hi, 0x40000040;\nmov.b64 da, {%32, hi};\nmov.b64 db, {%33, hi};\n"
        "wgmma.mma_async.sync.aligned.m64n64k16.f32.bf16.bf16 {%0, %1, %2, %3, %4, %5, %6, %7, %8, %9, %10, %11, %12, %13, %14, %15, %16, %17, %18, %19, %20, %21, %22, %23, %24, %25, %26, %27, %28, %29, %30, %31}, da, db, p, 1, 1, 0, 0;\n}\n"
        : "+f"(d[OFF + 0]), "+f"(d[OFF + 1]), "+f"(d[OFF + 2]), "+f"(d[OFF + 3]), "+f"(d[OFF + 4]), "+f"(d[OFF + 5]), "+f"(d[OFF + 6]), "+f"(d[OFF + 7]),
          "+f"(d[OFF + 8]), "+f"(d[OFF + 9]), "+f"(d[OFF + 10]), "+f"(d[OFF + 11]), "+f"(d[OFF + 12]), "+f"(d[OFF + 13]), "+f"(d[OFF + 14]), "+f"(d[OFF + 15]),
          "+f"(d[OFF + 16]), "+f"(d[OFF + 17]), "+f"(d[OFF + 18]), "+f"(d[OFF + 19]), "+f"(d[OFF + 20]), "+f"(d[OFF + 21]), "+f"(d[OFF + 22]), "+f"(d[OFF + 23]),
          "+f"(d[OFF + 24]), "+f"(d[OFF + 25]), "+f"(d[OFF + 26]), "+f"(d[OFF + 27]), "+f"(d[OFF + 28]), "+f"(d[OFF + 29]), "+f"(d[OFF + 30]), "+f"(d[OFF + 31])
        : "r"(descA), "r"(descB));
}

template <int OFF = 0> __device__ __forceinline__ void wgmma_n64_ss_tb0_z(float (&d)[64], uint32_t descA, uint32_t descB) {
    asm volatile("{\n.reg .pred p;\n.reg .b32 hi;\n.reg .b64 da, db;\nsetp.ne.b32 p, 0, 0;\nmov.b32 hi, 0x40000040;\nmov.b64 da, {%32, hi};\nmov.b64 db, {%33, hi};\n"
        "wgmma.mma_async.sync.aligned.m64n64k16.f32.bf16.bf16 {%0, %1, %2, %3, %4, %5, %6, %7, %8, %9, %10, %11, %12, %13, %14, %15, %16, %17, %18, %19, %20, %21, %22, %23, %24, %25, %26, %27, %28, %29, %30, %31}, da, db, p, 1, 1, 0, 0;\n}\n"
        : "=f"(d[OFF + 0]), "=f"(d[OFF + 1]), "=f"(d[OFF + 2]), "=f"(d[OFF + 3]), "=f"(d[OFF + 4]), "=f"(d[OFF + 5]), "=f"(d[OFF + 6]), "=f"(d[OFF + 7]),
          "=f"(d[OFF + 8]), "=f"(d[OFF + 9]), "=f"(d[OFF + 10]), "=f"(d[OFF + 11]), "=f"(d[OFF + 12]), "=f"(d[OFF + 13]), "=f"(d[OFF + 14]), "=f"(d[OFF + 15]),
          "=f"(d[OFF + 16]), "=f"(d[OFF + 17]), "=f"(d[OFF + 18]), "=f"(d[OFF + 19]), "=f"(d[OFF + 20]), "=f"(d[OFF + 21]), "=f"(d[OFF + 22]), "=f"(d[OFF + 23]),
          "=f"(d[OFF + 24]), "=f"(d[OFF + 25]), "=f"(d[OFF + 26]), "=f"(d[OFF + 27]), "=f"(d[OFF + 28]), "=f"(d[OFF + 29]), "=f"(d[OFF + 30]), "=f"(d[OFF + 31])
        : "r"(descA), "r"(descB));
}

template <int OFF = 0> __device__ __forceinline__ void wgmma_n256_rs_tb1(float (&d)[128], uint32_t a0, uint32_t a1, uint32_t a2, uint32_t a3, uint32_t descB) {
    asm volatile("{\n.reg .pred p;\n.reg .b32 hi;\n.reg .b64 db;\nsetp.ne.b32 p, 1, 0;\nmov.b32 hi, 0x40000040;\nmov.b64 db, {%132, hi};\n"
        "wgmma.mma_async.sync.aligned.m64n256k16.f32.bf16.bf16 {%0, %1, %2, %3, %4, %5, %6, %7, %8, %9, %10, %11, %12, %13, %14, %15, %16, %17, %18, %19, %20, %21, %22, %23, %24, %25, %26, %27, %28, %29, %30, %31, %32, %33, %34, %35, %36, %37, %38, %39, %40, %41, %42, %43, %44, %45, %46, %47, %48, %49, %50, %51, %52, %53, %54, %55, %56, %57, %58, %59, %60, %61, %62, %63, %64, %65, %66, %67, %68, %69, %70, %71, %72, %73, %74, %75, %76, %77, %78, %79, %80, %81, %82, %83, %84, %85, %86, %87, %88, %89, %90, %91, %92, %93, %94, %95, %96, %97, %98, %99, %100, %101, %102, %103, %104, %105, %106, %107, %108, %109, %110, %111, %112, %113, %114, %115, %116, %117, %118, %119, %120, %121, %122, %123, %124, %125, %126, %127}, {%128, %129, %130, %131}, db, p, 1, 1, 1;\n}\n"
        : "+f"(d[OFF + 0]), "+f"(d[OFF + 1]), "+f"(d[OFF + 2]), "+f"(d[OFF + 3]), "+f"(d[OFF + 4]), "+f"(d[OFF + 5]), "+f"(d[OFF + 6]), "+f"(d[OFF + 7]),
          "+f"(d[OFF + 8]), "+f"(d[OFF + 9]), "+f"(d[OFF + 10]), "+f"(d[OFF + 11]), "+f"(d[OFF + 12]), "+f"(d[OFF + 13]), "+f"(d[OFF + 14]), "+f"(d[OFF + 15]),
          "+f"(d[OFF + 16]), "+f"(d[OFF + 17]), "+f"(d[OFF + 18]), "+f"(d[OFF + 19]), "+f"(d[OFF + 20]), "+f"(d[OFF + 21]), "+f"(d[OFF + 22]), "+f"(d[OFF + 23]),
          "+f"(d[OFF + 24]), "+f"(d[OFF + 25]), "+f"(d[OFF + 26]), "+f"(d[OFF + 27]), "+f"(d[OFF + 28]), "+f"(d[OFF + 29]), "+f"(d[OFF + 30]), "+f"(d[OFF + 31]),
          "+f"(d[OFF + 32]), "+f"(d[OFF + 33]), "+f"(d[OFF + 34]), "+f"(d[OFF + 35]), "+f"(d[OFF + 36]), "+f"(d[OFF + 37]), "+f"(d[OFF + 38]), "+f"(d[OFF + 39]),
          "+f"(d[OFF + 40]), "+f"(d[OFF + 41]), "+f"(d[OFF + 42]), "+f"(d[OFF + 43]), "+f"(d[OFF + 44]), "+f"(d[OFF + 45]), "+f"(d[OFF + 46]), "+f"(d[OFF + 47]),
          "+f"(d[OFF + 48]), "+f"(d[OFF + 49]), "+f"(d[OFF + 50]), "+f"(d[OFF + 51]), "+f"(d[OFF + 52]), "+f"(d[OFF + 53]), "+f"(d[OFF + 54]), "+f"(d[OFF + 55]),
          "+f"(d[OFF + 56]), "+f"(d[OFF + 57]), "+f"(d[OFF + 58]), "+f"(d[OFF + 59]), "+f"(d[OFF + 60]), "+f"(d[OFF + 61]), "+f"(d[OFF + 62]), "+f"(d[OFF + 63]),
          "+f"(d[OFF + 64]), "+f"(d[OFF + 65]), "+f"(d[OFF + 66]), "+f"(d[OFF + 67]), "+f"(d[OFF + 68]), "+f"(d[OFF + 69]), "+f"(d[OFF + 70]), "+f"(d[OFF + 71]),
          "+f"(d[OFF + 72]), "+f"(d[OFF + 73]), "+f"(d[OFF + 74]), "+f"(d[OFF + 75]), "+f"(d[OFF + 76]), "+f"(d[OFF + 77]), "+f"(d[OFF + 78]), "+f"(d[OFF + 79]),
          "+f"(d[OFF + 80]), "+f"(d[OFF + 81]), "+f"(d[OFF + 82]), "+f"(d[OFF + 83]), "+f"(d[OFF + 84]), "+f"(d[OFF + 85]), "+f"(d[OFF + 86]), "+f"(d[OFF + 87]),
          "+f"(d[OFF + 88]), "+f"(d[OFF + 89]), "+f"(d[OFF + 90]), "+f"(d[OFF + 91]), "+f"(d[OFF + 92]), "+f"(d[OFF + 93]), "+f"(d[OFF + 94]), "+f"(d[OFF + 95]),
          "+f"(d[OFF + 96]), "+f"(d[OFF + 97]), "+f"(d[OFF + 98]), "+f"(d[OFF + 99]), "+f"(d[OFF + 100]), "+f"(d[OFF + 101]), "+f"(d[OFF + 102]), "+f"(d[OFF + 103]),
          "+f"(d[OFF + 104]), "+f"(d[OFF + 105]), "+f"(d[OFF + 106]), "+f"(d[OFF + 107]), "+f"(d[OFF + 108]), "+f"(d[OFF + 109]), "+f"(d[OFF + 110]), "+f"(d[OFF + 111]),
          "+f"(d[OFF + 112]), "+f"(d[OFF + 113]), "+f"(d[OFF + 114]), "+f"(d[OFF + 115]), "+f"(d[OFF + 116]), "+f"(d[OFF + 117]), "+f"(d[OFF + 118]), "+f"(d[OFF + 119]),
          "+f"(d[OFF + 120]), "+f"(d[OFF + 121]), "+f"(d[OFF + 122]), "+f"(d[OFF + 123]), "+f"(d[OFF + 124]), "+f"(d[OFF + 125]), "+f"(d[OFF + 126]), "+f"(d[OFF + 127])
        : "r"(a0), "r"(a1), "r"(a2), "r"(a3), "r"(descB));
}

template <int OFF = 0> __device__ __forceinline__ void wgmma_n256_rs_tb1_z(float (&d)[128], uint32_t a0, uint32_t a1, uint32_t a2, uint32_t a3, uint32_t descB) {
    asm volatile("{\n.reg .pred p;\n.reg .b32 hi;\n.reg .b64 db;\nsetp.ne.b32 p, 0, 0;\nmov.b32 hi, 0x40000040;\nmov.b64 db, {%132, hi};\n"
        "wgmma.mma_async.sync.aligned.m64n256k16.f32.bf16.bf16 {%0, %1, %2, %3, %4, %5, %6, %7, %8, %9, %10, %11, %12, %13, %14, %15, %16, %17, %18, %19, %20, %21, %22, %23, %24, %25, %26, %27, %28, %29, %30, %31, %32, %33, %34, %35, %36, %37, %38, %39, %40, %41, %42, %43, %44, %45, %46, %47, %48, %49, %50, %51, %52, %53, %54, %55, %56, %57, %58, %59, %60, %61, %62, %63, %64, %65, %66, %67, %68, %69, %70, %71, %72, %73, %74, %75, %76, %77, %78, %79, %80, %81, %82, %83, %84, %85, %86, %87, %88, %89, %90, %91, %92, %93, %94, %95, %96, %97, %98, %99, %100, %101, %102, %103, %104, %105, %106, %107, %108, %109, %110, %111, %112, %113, %114, %115, %116, %117, %118, %119, %120, %121, %122, %123, %124, %125, %126, %127}, {%128, %129, %130, %131}, db, p, 1, 1, 1;\n}\n"
        : "=f"(d[OFF + 0]), "=f"(d[OFF + 1]), "=f"(d[OFF + 2]), "=f"(d[OFF + 3]), "=f"(d[OFF + 4]), "=f"(d[OFF + 5]), "=f"(d[OFF + 6]), "=f"(d[OFF + 7]),
          "=f"(d[OFF + 8]), "=f"(d[OFF + 9]), "=f"(d[OFF + 10]), "=f"(d[OFF + 11]), "=f"(d[OFF + 12]), "=f"(d[OFF + 13]), "=f"(d[OFF + 14]), "=f"(d[OFF + 15]),
          "=f"(d[OFF + 16]), "=f"(d[OFF + 17]), "=f"(d[OFF + 18]), "=f"(d[OFF + 19]), "=f"(d[OFF + 20]), "=f"(d[OFF + 21]), "=f"(d[OFF + 22]), "=f"(d[OFF + 23]),
          "=f"(d[OFF + 24]), "=f"(d[OFF + 25]), "=f"(d[OFF + 26]), "=f"(d[OFF + 27]), "=f"(d[OFF + 28]), "=f"(d[OFF + 29]), "=f"(d[OFF + 30]), "=f"(d[OFF + 31]),
          "=f"(d[OFF + 32]), "=f"(d[OFF + 33]), "=f"(d[OFF + 34]), "=f"(d[OFF + 35]), "=f"(d[OFF + 36]), "=f"(d[OFF + 37]), "=f"(d[OFF + 38]), "=f"(d[OFF + 39]),
          "=f"(d[OFF + 40]), "=f"(d[OFF + 41]), "=f"(d[OFF + 42]), "=f"(d[OFF + 43]), "=f"(d[OFF + 44]), "=f"(d[OFF + 45]), "=f"(d[OFF + 46]), "=f"(d[OFF + 47]),
          "=f"(d[OFF + 48]), "=f"(d[OFF + 49]), "=f"(d[OFF + 50]), "=f"(d[OFF + 51]), "=f"(d[OFF + 52]), "=f"(d[OFF + 53]), "=f"(d[OFF + 54]), "=f"(d[OFF + 55]),
          "=f"(d[OFF + 56]), "=f"(d[OFF + 57]), "=f"(d[OFF + 58]), "=f"(d[OFF + 59]), "=f"(d[OFF + 60]), "=f"(d[OFF + 61]), "=f"(d[OFF + 62]), "=f"(d[OFF + 63]),
          "=f"(d[OFF + 64]), "=f"(d[OFF + 65]), "=f"(d[OFF + 66]), "=f"(d[OFF + 67]), "=f"(d[OFF + 68]), "=f"(d[OFF + 69]), "=f"(d[OFF + 70]), "=f"(d[OFF + 71]),
          "=f"(d[OFF + 72]), "=f"(d[OFF + 73]), "=f"(d[OFF + 74]), "=f"(d[OFF + 75]), "=f"(d[OFF + 76]), "=f"(d[OFF + 77]), "=f"(d[OFF + 78]), "=f"(d[OFF + 79]),
          "=f"(d[OFF + 80]), "=f"(d[OFF + 81]), "=f"(d[OFF + 82]), "=f"(d[OFF + 83]), "=f"(d[OFF + 84]), "=f"(d[OFF + 85]), "=f"(d[OFF + 86]), "=f"(d[OFF + 87]),
          "=f"(d[OFF + 88]), "=f"(d[OFF + 89]), "=f"(d[OFF + 90]), "=f"(d[OFF + 91]), "=f"(d[OFF + 92]), "=f"(d[OFF + 93]), "=f"(d[OFF + 94]), "=f"(d[OFF + 95]),
          "=f"(d[OFF + 96]), "=f"(d[OFF + 97]), "=f"(d[OFF + 98]), "=f"(d[OFF + 99]), "=f"(d[OFF + 100]), "=f"(d[OFF + 101]), "=f"(d[OFF + 102]), "=f"(d[OFF + 103]),
          "=f"(d[OFF + 104]), "=f"(d[OFF + 105]), "=f"(d[OFF + 106]), "=f"(d[OFF + 107]), "=f"(d[OFF + 108]), "=f"(d[OFF + 109]), "=f"(d[OFF + 110]), "=f"(d[OFF + 111]),
          "=f"(d[OFF + 112]), "=f"(d[OFF + 113]), "=f"(d[OFF + 114]), "=f"(d[OFF + 115]), "=f"(d[OFF + 116]), "=f"(d[OFF + 117]), "=f"(d[OFF + 118]), "=f"(d[OFF + 119]),
          "=f"(d[OFF + 120]), "=f"(d[OFF + 121]), "=f"(d[OFF + 122]), "=f"(d[OFF + 123]), "=f"(d[OFF + 124]), "=f"(d[OFF + 125]), "=f"(d[OFF + 126]), "=f"(d[OFF + 127])
        : "r"(a0), "r"(a1), "r"(a2), "r"(a3), "r"(descB));
}

template <int OFF = 0> __device__ __forceinline__ void wgmma_n64_rs_tb1(float (&d)[128], uint32_t a0, uint32_t a1, uint32_t a2, uint32_t a3, uint32_t descB) {
    asm volatile("{\n.reg .pred p;\n.reg .b32 hi;\n.reg .b64 db;\nsetp.ne.b32 p, 1, 0;\nmov.b32 hi, 0x40000040;\nmov.b64 db, {%36, hi};\n"
        "wgmma.mma_async.sync.aligned.m64n64k16.f32.bf16.bf16 {%0, %1, %2, %3, %4, %5, %6, %7, %8, %9, %10, %11, %12, %13, %14, %15, %16, %17, %18, %19, %20, %21, %22, %23, %24, %25, %26, %27, %28, %29, %30, %31}, {%32, %33, %34, %35}, db, p, 1, 1, 1;\n}\n"
        : "+f"(d[OFF + 0]), "+f"(d[OFF + 1]), "+f"(d[OFF + 2]), "+f"(d[OFF + 3]), "+f"(d[OFF + 4]), "+f"(d[OFF + 5]), "+f"(d[OFF + 6]), "+f"(d[OFF + 7]),
          "+f"(d[OFF + 8]), "+f"(d[OFF + 9]), "+f"(d[OFF + 10]), "+f"(d[OFF + 11]), "+f"(d[OFF + 12]), "+f"(d[OFF + 13]), "+f"(d[OFF + 14]), "+f"(d[OFF + 15]),
          "+f"(d[OFF + 16]), "+f"(d[OFF + 17]), "+f"(d[OFF + 18]), "+f"(d[OFF + 19]), "+f"(d[OFF + 20]), "+f"(d[OFF + 21]), "+f"(d[OFF + 22]), "+f"(d[OFF + 23]),
          "+f"(d[OFF + 24]), "+f"(d[OFF + 25]), "+f"(d[OFF + 26]), "+f"(d[OFF + 27]), "+f"(d[OFF + 28]), "+f"(d[OFF + 29]), "+f"(d[OFF + 30]), "+f"(d[OFF + 31])
        : "r"(a0), "r"(a1), "r"(a2), "r"(a3), "r"(descB));
}

template <int OFF = 0> __device__ __forceinline__ void wgmma_n64_rs_tb1_z(float (&d)[128], uint32_t a0, uint32_t a1, uint32_t a2, uint32_t a3, uint32_t descB) {
    asm volatile("{\n.reg .pred p;\n.reg .b32 hi;\n.reg .b64 db;\nsetp.ne.b32 p, 0, 0;\nmov.b32 hi, 0x40000040;\nmov.b64 db, {%36, hi};\n"
        "wgmma.mma_async.sync.aligned.m64n64k16.f32.bf16.bf16 {%0, %1, %2, %3, %4, %5, %6, %7, %8, %9, %10, %11, %12, %13, %14, %15, %16, %17, %18, %19, %20, %21, %22, %23, %24, %25, %26, %27, %28, %29, %30, %31}, {%32, %33, %34, %35}, db, p, 1, 1, 1;\n}\n"
        : "=f"(d[OFF + 0]), "=f"(d[OFF + 1]), "=f"(d[OFF + 2]), "=f"(d[OFF + 3]), "=f"(d[OFF + 4]), "=f"(d[OFF + 5]), "=f"(d[OFF + 6]), "=f"(d[OFF + 7]),
          "=f"(d[OFF + 8]), "=f"(d[OFF + 9]), "=f"(d[OFF + 10]), "=f"(d[OFF + 11]), "=f"(d[OFF + 12]), "=f"(d[OFF + 13]), "=f"(d[OFF + 14]), "=f"(d[OFF + 15]),
          "=f"(d[OFF + 16]), "=f"(d[OFF + 17]), "=f"(d[OFF + 18]), "=f"(d[OFF + 19]), "=f"(d[OFF + 20]), "=f"(d[OFF + 21]), "=f"(d[OFF + 22]), "=f"(d[OFF + 23]),
          "=f"(d[OFF + 24]), "=f"(d[OFF + 25]), "=f"(d[OFF + 26]), "=f"(d[OFF + 27]), "=f"(d[OFF + 28]), "=f"(d[OFF + 29]), "=f"(d[OFF + 30]), "=f"(d[OFF + 31])
        : "r"(a0), "r"(a1), "r"(a2), "r"(a3), "r"(descB));
}

struct Ring {
    uint32_t slot, phase;
    __device__ __forceinline__ void next() {
        if (++slot == NSLOT) { slot = 0; phase ^= 1; }
    }
    __device__ __forceinline__ void uniform() {
        slot = __shfl_sync(0xffffffffu, slot, 0);
        phase = __shfl_sync(0xffffffffu, phase, 0);
    }
};

struct Cons {
    uint32_t sbase;
    uint32_t empty_tgt;
    uint32_t qb;
    int wg;
    uint32_t sph;
    Ring ring;

    __device__ __forceinline__ uint32_t wait_full() {
        uint32_t s = ring.slot;
        mbar_wait(sbase + BAR_OFF + s * 8, ring.phase);
        ring.next();
        return s;
    }
    __device__ __forceinline__ void release(uint32_t s) {
        if (empty_tgt != 0) mbar_arrive_cluster(empty_tgt + s * 8);
    }
    __device__ __forceinline__ bool leader() const { return (fresh_tid() & 127) == 0; }
    __device__ __forceinline__ void wg_bar() { bar_sync(3 + wg, 128); }
    template <int H> __device__ __forceinline__ void stage_acquire() {
        mbar_wait(sbase + SFREE_OFF + (wg * 2 + H) * 8, ((sph >> H) & 1) ^ 1);
    }
    template <int H, bool FENCE = true> __device__ __forceinline__ void stage_commit() {
        if (FENCE) fence_async_smem();
        __syncwarp();
        if ((fresh_tid() & 31) == 0) asm volatile("mbarrier.arrive.shared::cta.b64 _, [%0];" ::"r"(sbase + SFULL_OFF + (wg * 2 + H) * 8) : "memory");
        sph ^= 1 << H;
    }
};

struct Stager {
    uint32_t base, x;
    __device__ __forceinline__ Stager(const Cons& c) {
        const uint32_t t = fresh_tid(), lane = t & 31;
        const uint32_t r = ((t >> 5) & 3) * 16 + (lane & 7) + ((lane >> 3) & 1) * 8;
        base = c.qb + r * 128;
        x = ((lane >> 4) ^ (r & 7)) << 4;
    }
    __device__ __forceinline__ void put(int blk, int j4, uint32_t r0, uint32_t r1, uint32_t r2, uint32_t r3) const {
        stsm4(base + blk * 8192 + ((uint32_t)(j4 << 5) ^ x), r0, r1, r2, r3);
    }
};

template <int N, bool FIRST>
__device__ __forceinline__ void gemm_kstep(float (&acc)[128], uint32_t da, uint32_t db) {
    wg_fence();
#pragma unroll
    for (int kk = 0; kk < 4; kk++) {
        if constexpr (N == 256) {
            if (FIRST && kk == 0) wgmma_n256_ss_tb1_z(acc, da, db);
            else wgmma_n256_ss_tb1(acc, da + kk * 2, db + kk * 128);
        } else {
            if (FIRST && kk == 0) wgmma_n192_ss_tb1_z(acc, da, db);
            else wgmma_n192_ss_tb1(acc, da + kk * 2, db + kk * 128);
        }
    }
    wg_commit();
}

template <int N>
__device__ __forceinline__ void gemm_mainloop(Cons& c, float (&acc)[128], int nk, int lead) {
    uint32_t prevB = c.wait_full();
    uint32_t sa = c.wait_full();
    uint32_t prevA = 0xffffffffu;
    gemm_kstep<N, true>(acc, make_desc(c.sbase + sa * SLOT_BYTES + c.wg * 16384, 16, 1024), make_desc(c.sbase + prevB * SLOT_BYTES, 8192, 1024));
    auto step = [&](int k) -> uint32_t {
        uint32_t sb = c.wait_full();
        if ((k & 1) == 0) sa = c.wait_full();
        gemm_kstep<N, false>(acc, make_desc(c.sbase + sa * SLOT_BYTES + c.wg * 16384 + (k & 1) * 8192, 16, 1024),
                             make_desc(c.sbase + sb * SLOT_BYTES, 8192, 1024));
        return sb;
    };
    for (int k = 1; k < nk - 2; k++) {
        uint32_t sb = step(k);
        wg_wait<1>();
        if (prevA != 0xffffffffu) c.release(prevA);
        c.release(prevB);
        prevB = sb;
        prevA = (k & 1) ? sa : 0xffffffffu;
    }
    if (c.wg != lead) {
        wg_wait<0>();
        if (prevA != 0xffffffffu) c.release(prevA);
        c.release(prevB);
        bar_sync(7, 256);
        prevB = step(nk - 2);
    } else {
        const uint32_t sb2 = step(nk - 2);
        wg_wait<1>();
        if (prevA != 0xffffffffu) c.release(prevA);
        c.release(prevB);
        prevB = sb2;
    }
    prevA = sa;
    uint32_t sb = step(nk - 1);
    if (c.wg == lead) bar_arrive(7, 256);
    wg_wait<1>();
    if (prevA != sa) c.release(prevA);
    c.release(prevB);
    wg_wait<0>();
    c.release(sb);
    c.release(sa);
}

template <int NC, int OFF, int H>
__device__ __forceinline__ void stage_plain(Cons& c, const float (&acc)[128]) {
    const Stager st(c);
    c.stage_acquire<H>();
#pragma unroll
    for (int j = 0; j < NC / 16; j++)
        st.put(H * 2 + (j >> 2), j & 3, pack_bf16(acc[OFF + j * 8 + 0], acc[OFF + j * 8 + 1]), pack_bf16(acc[OFF + j * 8 + 2], acc[OFF + j * 8 + 3]),
               pack_bf16(acc[OFF + j * 8 + 4], acc[OFF + j * 8 + 5]), pack_bf16(acc[OFF + j * 8 + 6], acc[OFF + j * 8 + 7]));
}

__device__ __forceinline__ int mask_d() {
    const int t = fresh_tid();
    return ((t >> 5) & 3) * 16 + ((t & 31) >> 2) - (t & 3) * 2;
}
__device__ __forceinline__ float quad_max(float v) {
    v = fmaxf(v, __shfl_xor_sync(0xffffffffu, v, 1));
    return fmaxf(v, __shfl_xor_sync(0xffffffffu, v, 2));
}
constexpr float SM_C = 0.0625f * 1.4426950408889634f;

template <int NK, int MASK>
__device__ __forceinline__ void attn_step(Cons& c, float (&o)[128], float& m0, float& m1, float& l0, float& l1,
                                          bool sync_a, bool sig_a, bool sig_b) {
    float s[64];
    const int myT = 1 + c.wg, otT = 2 - c.wg;
    if (sync_a) bar_sync(myT, 256);
    uint32_t ska = c.wait_full();
    const uint32_t dq = make_desc(c.qb + (ska & ~7u), 16, 1024);
    {
        uint32_t dk = make_desc(c.sbase + ska * SLOT_BYTES, 16, 1024);
        wg_fence();
#pragma unroll
        for (int k = 0; k < 8; k++) {
            uint32_t a = dq + (k >> 2) * 512 + (k & 3) * 2, b = dk + (k >> 2) * 1024 + (k & 3) * 2;
            if constexpr (NK == 128) { if (k == 0) wgmma_n128_ss_tb0_z(s, a, b); else wgmma_n128_ss_tb0(s, a, b); }
            else { if (k == 0) wgmma_n64_ss_tb0_z(s, a, b); else wgmma_n64_ss_tb0(s, a, b); }
        }
    }
    wg_commit();
    uint32_t skb = c.wait_full();
    {
        uint32_t dk = make_desc(c.sbase + skb * SLOT_BYTES, 16, 1024);
        wg_fence();
#pragma unroll
        for (int k = 0; k < 8; k++) {
            uint32_t a = dq + (2 + (k >> 2)) * 512 + (k & 3) * 2, b = dk + (k >> 2) * 1024 + (k & 3) * 2;
            if constexpr (NK == 128) wgmma_n128_ss_tb0(s, a, b);
            else wgmma_n64_ss_tb0(s, a, b);
        }
    }
    wg_commit();
    if (sig_a) bar_arrive(otT, 256);
    wg_wait<1>();
    c.release(ska);
    wg_wait<0>();
    c.release(skb);

    constexpr int NS = NK / 2;
    uint32_t p[NS / 2], dep = 0;
    if constexpr (MASK != 0) {
        constexpr int MI0 = (MASK == 2) ? 8 : 0;
        {
            const int d = mask_d();
#pragma unroll
            for (int i = MI0; i < NS / 4; i++)
#pragma unroll
                for (int e = 0; e < 4; e++)
                    if ((i - MI0) * 8 + (e & 1) - 8 * (e >> 1) > d) s[i * 4 + e] = -INFINITY;
            float t0 = fmaxf(s[0], s[1]), t1 = fmaxf(s[2], s[3]);
            float u0 = fmaxf(s[4], s[5]), u1 = fmaxf(s[6], s[7]);
#pragma unroll
            for (int i = 2; i < NS / 4; i += 2) {
                t0 = fmaxf(t0, fmaxf(s[i * 4 + 0], s[i * 4 + 1]));
                t1 = fmaxf(t1, fmaxf(s[i * 4 + 2], s[i * 4 + 3]));
                u0 = fmaxf(u0, fmaxf(s[i * 4 + 4], s[i * 4 + 5]));
                u1 = fmaxf(u1, fmaxf(s[i * 4 + 6], s[i * 4 + 7]));
            }
            m0 = quad_max(fmaxf(t0, u0)) * SM_C;
            m1 = quad_max(fmaxf(t1, u1)) * SM_C;
        }
        l0 = 0.f; l1 = 0.f;
#pragma unroll
        for (int i = 0; i < NS / 4; i++) {
            float e0 = ex2(fmaf(s[i * 4 + 0], SM_C, -m0)), e1 = ex2(fmaf(s[i * 4 + 1], SM_C, -m0));
            float e2 = ex2(fmaf(s[i * 4 + 2], SM_C, -m1)), e3 = ex2(fmaf(s[i * 4 + 3], SM_C, -m1));
            l0 += e0 + e1; l1 += e2 + e3;
            p[i * 2 + 0] = pack_bf16(e0, e1);
            p[i * 2 + 1] = pack_bf16(e2, e3);
            if (i == 7) dep = (__float_as_uint(l0) | __float_as_uint(l1)) >> 31;
        }
    } else {
#pragma unroll
        for (int hf = 0; hf < 2; hf++) {
            float a0, a1;
#pragma unroll 1
            for (int pass = 0;; pass++) {
                a0 = 0.f; a1 = 0.f;
#pragma unroll
                for (int i = hf * 8; i < hf * 8 + 8; i++) {
                    float e0 = ex2(fmaf(s[i * 4 + 0], SM_C, -m0)), e1 = ex2(fmaf(s[i * 4 + 1], SM_C, -m0));
                    float e2 = ex2(fmaf(s[i * 4 + 2], SM_C, -m1)), e3 = ex2(fmaf(s[i * 4 + 3], SM_C, -m1));
                    a0 += e0 + e1; a1 += e2 + e3;
                    p[i * 2 + 0] = pack_bf16(e0, e1);
                    p[i * 2 + 1] = pack_bf16(e2, e3);
                }
                if (!__any_sync(0xffffffffu, a0 + a1 >= 1.0995116e12f) || pass) break;
                float t0 = fmaxf(s[hf * 32 + 0], s[hf * 32 + 1]), t1 = fmaxf(s[hf * 32 + 2], s[hf * 32 + 3]);
#pragma unroll
                for (int i = hf * 8 + 1; i < hf * 8 + 8; i++) {
                    t0 = fmaxf(t0, fmaxf(s[i * 4 + 0], s[i * 4 + 1]));
                    t1 = fmaxf(t1, fmaxf(s[i * 4 + 2], s[i * 4 + 3]));
                }
                t0 = ceilf(fmaxf(fmaf(quad_max(t0), SM_C, -m0), 0.f));
                t1 = ceilf(fmaxf(fmaf(quad_max(t1), SM_C, -m1), 0.f));
                const float sc0 = ex2(-t0), sc1 = ex2(-t1);
                m0 += t0; m1 += t1;
                l0 *= sc0; l1 *= sc1;
#pragma unroll
                for (int i = 0; i < 32; i++) {
                    o[i * 4 + 0] *= sc0; o[i * 4 + 1] *= sc0;
                    o[i * 4 + 2] *= sc1; o[i * 4 + 3] *= sc1;
                }
                if (hf == 1) {
#pragma unroll
                    for (int i = 0; i < 8; i++) {
                        p[i * 2 + 0] = pack_bf16(bf_lo(p[i * 2 + 0]) * sc0, bf_hi(p[i * 2 + 0]) * sc0);
                        p[i * 2 + 1] = pack_bf16(bf_lo(p[i * 2 + 1]) * sc1, bf_hi(p[i * 2 + 1]) * sc1);
                    }
                }
            }
            l0 += a0; l1 += a1;
        }
    }
    uint32_t sva = c.wait_full();
    {
        uint32_t dv = make_desc(c.sbase + sva * SLOT_BYTES, 8192, 1024) + dep;
        wg_fence();
#pragma unroll
        for (int k = 0; k < 4; k++) {
            if (MASK != 0 && k == 0) wgmma_n256_rs_tb1_z(o, p[0], p[1], p[2], p[3], dv);
            else wgmma_n256_rs_tb1(o, p[k * 4 + 0], p[k * 4 + 1], p[k * 4 + 2], p[k * 4 + 3], dv + k * 128);
        }
        wg_commit();
    }
    uint32_t svb = c.wait_full();
    if constexpr (NK == 128) {
        uint32_t dv = make_desc(c.sbase + svb * SLOT_BYTES, 8192, 1024) + (MASK ? (__float_as_uint(l0) | __float_as_uint(l1)) >> 31 : 0);
        wg_fence();
#pragma unroll
        for (int k = 4; k < 8; k++) wgmma_n256_rs_tb1(o, p[k * 4 + 0], p[k * 4 + 1], p[k * 4 + 2], p[k * 4 + 3], dv + (k - 4) * 128);
        wg_commit();
    }
    if (sig_b) bar_arrive(otT, 256);
    if constexpr (NK == 128) {
        wg_wait<1>();
        c.release(sva);
        wg_wait<0>();
    } else {
        wg_wait<0>();
        c.release(sva);
    }
    c.release(svb);
}

template <int OFF, bool FIRST>
__device__ __forceinline__ uint32_t oproj_mma(Cons& c, float (&acc)[128], const uint32_t (&a)[64]) {
    const uint32_t s0 = c.wait_full();
    const uint32_t d0 = make_desc(c.sbase + s0 * SLOT_BYTES, 16384, 1024);
    wg_fence();
#pragma unroll
    for (int k = 0; k < 16; k++) {
        if (FIRST && k == 0) wgmma_n64_rs_tb1_z<OFF>(acc, a[0], a[1], a[2], a[3], d0);
        else wgmma_n64_rs_tb1<OFF>(acc, a[k * 4 + 0], a[k * 4 + 1], a[k * 4 + 2], a[k * 4 + 3], d0 + k * 128);
    }
    wg_commit();
    return s0;
}
template <int C>
__device__ __forceinline__ uint32_t oproj_chunk(Cons& c, float (&acc)[128], const uint32_t (&a)[64], const uint32_t (&b)[64], uint32_t prev) {
    const uint32_t s0 = oproj_mma<(C & 1) * 32, true>(c, acc, a);
    if constexpr (C > 0) {
        wg_wait<1>();
        c.release(prev);
        stage_plain<64, ((C - 1) & 1) * 32, (C - 1) & 1>(c, acc);
        c.stage_commit<(C - 1) & 1>();
    }
    const uint32_t s1 = oproj_mma<(C & 1) * 32, false>(c, acc, b);
    wg_wait<1>();
    c.release(s0);
    return s1;
}

__device__ __forceinline__ uint32_t fin2(float s0, float s1, uint32_t g, uint32_t x) {
    float g0, g1;
    silu2(bf_lo(g), bf_hi(g), g0, g1);
    bf16r2(g0, g1);
    bf16r2(s0, s1);
    s0 *= g0; s1 *= g1;
    bf16r2(s0, s1);
    return pack_bf16(bf_lo(x) + s0, bf_hi(x) + s1);
}
__device__ __forceinline__ void finalize_slot(Cons& c, const Params& P, int row, int u) {
    const uint32_t s = c.wait_full();
    const int t = fresh_tid();
    const uint32_t a = c.sbase + s * SLOT_BYTES + t * 8;
    uint2 v[10];
#pragma unroll
    for (int i = 0; i < 10; i++) asm volatile("ld.shared.v2.u32 {%0, %1}, [%2];" : "=r"(v[i].x), "=r"(v[i].y) : "r"(a + i * 2048) : "memory");
    float a0 = 0.f, a1 = 0.f, a2 = 0.f, a3 = 0.f;
#pragma unroll
    for (int i = 0; i < 8; i++) { a0 += bf_lo(v[i].x); a1 += bf_hi(v[i].x); a2 += bf_lo(v[i].y); a3 += bf_hi(v[i].y); }
    uint2 r;
    r.x = fin2(a0, a1, v[9].x, v[8].x);
    r.y = fin2(a2, a3, v[9].y, v[8].y);
    *(uint2*)(P.out + (size_t)(row + (t >> 4)) * DM + u * 64 + (t & 15) * 4) = r;
    __syncwarp();
    if (u < 7 - NSLOT) c.release(s);
}

__global__ void __cluster_dims__(2, 1, 1) __launch_bounds__(384, 1) fused_kernel(const __grid_constant__ Params P) {
    extern __shared__ __align__(1024) uint8_t smem_raw[];
    const uint32_t sbase = (smem_u32(smem_raw) + 1023) & ~1023u;
    const uint32_t full0 = sbase + BAR_OFF, empty0 = full0 + 8 * NSLOT, done_bar = full0 + 16 * NSLOT;
    const int warp = __shfl_sync(0xffffffffu, (int)(threadIdx.x >> 5), 0);
    const int cl = blockIdx.x >> 1;
    const uint32_t rank = blockIdx.x & 1;

    if (threadIdx.x == 0) {
        for (int i = 0; i < NSLOT; i++) {
            mbar_init(full0 + i * 8, 1);
            mbar_init(empty0 + i * 8, 16);
        }
        mbar_init(done_bar, 11);
        mbar_init(done_bar + 8, 8);
        for (int i = 0; i < 4; i++) {
            mbar_init(sbase + SFULL_OFF + i * 8, 4);
            mbar_init(sbase + SFREE_OFF + i * 8, 1);
        }
        asm volatile("fence.mbarrier_init.release.cluster;" ::: "memory");
    }
    if (warp == 8 && (threadIdx.x & 31) < 3) {
        const CUtensorMap* pm = (threadIdx.x & 31) == 0 ? &P.ckv : (threadIdx.x & 31) == 1 ? &P.wuk : &P.wuv;
        asm volatile("prefetch.tensormap [%0];" ::"l"((uint64_t)pm) : "memory");
    }
    __syncwarp();
    cluster_sync_relaxed();

    if (warp >= 8) {
        asm volatile("setmaxnreg.dec.sync.aligned.u32 24;");
        const int lane = fresh_tid() & 31;
        if (warp == 8) {
            Ring ring{0, 0};
            const bool el = lane == 0;
            const unsigned done0 = *(volatile unsigned*)&g_cnt[CNT_DONE];
            auto get_epoch = [&]() { return done0 / NCTA; };
            auto load_mc = [&](const CUtensorMap* mp, int c1, int c2) {
                mbar_wait(empty0 + ring.slot * 8, ring.phase ^ 1);
                if (el) {
                    mbar_expect_tx(full0 + ring.slot * 8, SLOT_BYTES);
                    tma_load_3d_mc(sbase + ring.slot * SLOT_BYTES + rank * 16384, mp, full0 + ring.slot * 8, 0, c1, c2);
                }
                ring.next();
            };
            auto wait_cnt = [&](int idx, unsigned n) {
                while ((int)(ld_acquire(&g_cnt[idx]) - (get_epoch() + 1) * n) < 0) __nanosleep(32);
                fence_async_all();
            };
            bool ln_ok = false;
#pragma unroll 1
            for (int it = 0; it < MAXITEMS; it++) {
                const uint32_t item = P.sched[cl][it];
                const int type = (item >> 12) & 7, ia = (item >> 6) & 63, ib = item & 63;
                if (type == IT_END) break;
                if ((type == IT_GU || type == IT_AT) && !ln_ok) { wait_cnt(CNT_LN, 128); ln_ok = true; }
                if (type == IT_DN) wait_cnt(CNT_GU + ia * 2 + rank, 28);
                const unsigned* fl = &g_cnt[CNT_KV + ((lane >> 4) * 16 + (ib & 15)) * 16 + (lane & 15)];
                unsigned rdy = 0;
                {
                    const int row0 = ia * 256 + rank * (type == IT_AT ? 64 : 128);
                    const int row1 = type == IT_AT ? ia * 256 + 192 - rank * 64 : row0 + 64;
                    const CUtensorMap* mA = type == IT_KV ? &P.ckv : type == IT_DN ? &P.h : &P.xn;
                    const CUtensorMap* mB = type == IT_KV ? (ib < 16 ? &P.wuk : &P.wuv) : type == IT_GU ? (rank == 0 ? &P.wg : &P.wu) : type == IT_DN ? &P.wd : &P.wq;
                    const int nb = type == IT_GU ? ib * 2 : (ib & 15) * 4 + rank * 2;
                    const int nk = type == IT_KV ? DC / 64 : type == IT_DN ? FF / 64 : DM / 64;
#pragma unroll 1
                    for (int k = 0; k < nk; k++) {
                        load_mc(mB, k * 64, nb);
                        if ((k & 1) == 0) {
                            mbar_wait(empty0 + ring.slot * 8, ring.phase ^ 1);
                            if (el) {
                                mbar_expect_tx(full0 + ring.slot * 8, SLOT_BYTES);
                                tma_load_3d(sbase + ring.slot * SLOT_BYTES, mA, full0 + ring.slot * 8, 0, row0, k);
                                tma_load_3d(sbase + ring.slot * SLOT_BYTES + 16384, mA, full0 + ring.slot * 8, 0, row1, k);
                            }
                            ring.next();
                        }
                    }
                }
                if (type == IT_AT) {
                    const int h = ib, nblk = 2 * ia + 2;
#pragma unroll 1
                    for (int j = nblk - 1; j >= 0; j--) {
#pragma unroll 1
                        for (int kv = 0; kv < 2; kv++) {
                            const int bit = kv * 16 + j;
                            if (((rdy >> bit) & 1) == 0) {
                                for (;;) {
                                    rdy = __ballot_sync(0xffffffffu, (int)(ld_acquire(fl) - (get_epoch() + 1) * 2) >= 0);
                                    if ((rdy >> bit) & 1) break;
                                    __nanosleep(64);
                                }
                                fence_async_all();
                            }
                            load_mc(kv ? &P.v_ld : &P.k_ld, j * 128, kv ? 64 + h * 4 + rank * 2 : h * 4 + rank);
                            load_mc(kv ? &P.v_ld : &P.k_ld, j * 128 + kv * 64, kv ? 64 + h * 4 + rank * 2 : h * 4 + 2 + rank);
                        }
                        if (h >= 8 && j == 1) {
                            const int ci = (h - 8) * 32 + ia * 4 + ((lane & 1) ? 3 - (int)rank : (int)rank);
                            while (!__all_sync(0xffffffffu, (int)(ld_acquire(&g_cnt[CNT_CTX + ci]) - (get_epoch() + 1)) >= 0)) __nanosleep(64);
                            if (lane < 2) asm volatile("cp.async.bulk.prefetch.L2.global [%0], 32768;" ::"l"(g_ctx + (size_t)ci * 2048) : "memory");
                        }
                    }
                    if (h >= 8) {
#pragma unroll 1
                        for (int t = 0; t < 14; t++) load_mc(&P.wo, (h - (t & 1) * 8) * 256 + rank * 128, t >> 1);
                        const int row = ia * 256 + ((h - 8) * 2 + rank) * 16;
                        const unsigned* cp = &g_cnt[(lane & 7) == 7 ? CNT_DN + (row >> 6) : CNT_P + (row >> 6) * 8 + (lane & 7)];
                        const unsigned tgt = (get_epoch() + 1) * ((lane & 7) == 7 ? 2 : 8);
                        rdy = 0;
#pragma unroll 1
                        for (int u = 0; u < 7; u++) {
                            mbar_wait(empty0 + ring.slot * 8, ring.phase ^ 1);
                            if (((rdy >> u) & (rdy >> 7) & 1) == 0) {
                                do { rdy = __ballot_sync(0xffffffffu, (int)(ld_acquire(cp) - tgt) >= 0); } while (((rdy >> u) & (rdy >> 7) & 1) == 0);
                                fence_async_all();
                            }
                            if (el) {
                                const uint32_t dst = sbase + ring.slot * SLOT_BYTES, bar = full0 + ring.slot * 8;
                                mbar_expect_tx(bar, 10 * 2048);
                                tma_load_3d(dst, &P.p_ld, bar, u * 64, row, 0);
                                tma_load_3d(dst + 8 * 2048, &P.x_ld, bar, u * 64, row, 0);
                                tma_load_3d(dst + 9 * 2048, &P.g_ld, bar, u * 64, row, 0);
                            }
                            ring.next();
                        }
                    }
                }
            }
            if (lane == 0) asm volatile("mbarrier.arrive.shared::cta.b64 _, [%0];" ::"r"(done_bar) : "memory");
        } else if (warp == 11) {
            if (blockIdx.x < 128) {
                uint32_t n = 0;
                while (!mbar_try(done_bar + 8, 0)) trap_if(++n > (1u << 18));
                if (lane == 0) { __threadfence(); fence_async_all(); red_release(&g_cnt[CNT_LN], 1); }
                __syncwarp();
            }
            if (lane == 0) {
                uint32_t n = 0;
                while (!mbar_try(done_bar, 0)) trap_if(++n > (1u << 18));
            }
        } else {
            const int w = warp - 9;
            uint32_t sph = 0;
#pragma unroll 1
            for (int it = 0; it < MAXITEMS; it++) {
                const uint32_t item = P.sched[cl][it];
                const int type = (item >> 12) & 7, ia = (item >> 6) & 63, ib = item & 63;
                if (type == IT_END) break;
                if (w == 1) {
                    const uint32_t nx = P.sched[cl][it + 1];
                    if (nx & 0x8000) {
                        const bool kvn = ((nx >> 12) & 7) == IT_KV;
                        const bf16* wp = (kvn ? ((nx & 16) ? P.pwuv : P.pwuk) : P.pwq) + (size_t)(lane >> 1) * 4096 + (nx & 15) * 256 + rank * 128 + (lane & 1) * 64;
#pragma unroll 1
                        for (int i = kvn ? 64 : 28; i > 0; i--) {
                            asm volatile("prefetch.global.L2 [%0];" ::"l"(wp) : "memory");
                            wp += 16 * 4096;
                            __nanosleep(80);
                        }
                    }
                    __syncwarp();
                }
                const int grp = type == IT_AT ? (w == 0 ? (int)rank : 3 - (int)rank) : (int)rank * 2 + w;
                const int row = ia * 256 + grp * 64 + (type == IT_AT ? (ib - 8) * SEQ : 0);
                const CUtensorMap* mp = type == IT_KV ? &P.v_ld : type == IT_GU ? &P.h : type == IT_DN ? &P.sg_st : &P.p_st;
                const int nb0 = type == IT_GU ? ib * 2 : type == IT_AT ? 0 : ib * 4;
                const int nst = type == IT_GU ? 1 : type == IT_AT ? (ib < 8 ? 1 : 7) : 2;
                const int flag = type == IT_KV ? CNT_KV + ib * 16 + ia * 2 + rank : type == IT_GU ? CNT_GU + ia * 2 + rank
                               : type == IT_DN ? CNT_DN + ia * 4 + grp : CNT_P + (ia * 4 + grp) * 8;
#pragma unroll 1
                for (int t = 0; t < nst; t++) {
                    const uint32_t hf = t & 1;
                    mbar_wait(sbase + SFULL_OFF + (w * 2 + hf) * 8, (sph >> hf) & 1);
                    sph ^= 1 << hf;
                    if (lane == 0) {
                        if (type == IT_AT && ib < 8) {
                            asm volatile("mbarrier.arrive.shared::cta.b64 _, [%0];" ::"r"(sbase + SFREE_OFF + (w * 2 + hf) * 8) : "memory");
                            __threadfence();
                            red_release(&g_cnt[CNT_CTX + ib * 32 + ia * 4 + grp], 1);
                        } else {
                            tma_store_3d(mp, sbase + QB_OFF + w * 32768 + hf * 16384, 0, row, type == IT_AT ? t : nb0 + t * 2);
                            bulk_commit();
                            if (type == IT_AT && t > 0) { bulk_wait<1>(); red_relaxed(&g_cnt[flag + t - 1]); }
                            bulk_wait_read<0>();
                            asm volatile("mbarrier.arrive.shared::cta.b64 _, [%0];" ::"r"(sbase + SFREE_OFF + (w * 2 + hf) * 8) : "memory");
                            if (t == nst - 1) {
                                bulk_wait<0>();
                                red_relaxed(&g_cnt[flag + (type == IT_AT ? t : 0)]);
                            }
                        }
                    }
                    __syncwarp();
                }
            }
            if (lane == 0) asm volatile("mbarrier.arrive.shared::cta.b64 _, [%0];" ::"r"(done_bar) : "memory");
        }
        __syncwarp();
        if (cl >= 64) cluster_sync_relaxed();
    } else {
        asm volatile("setmaxnreg.inc.sync.aligned.u32 240;");
        int lane = fresh_tid() & 31;
        Cons c;
        c.sbase = sbase;
        c.empty_tgt = lane < 2 ? mapa(empty0, lane) : 0;
        c.wg = warp >> 2;
        c.qb = sbase + QB_OFF + c.wg * 32768;
        c.sph = 0;
        c.ring = Ring{0, 0};

        constexpr int LR = 2;
        if (blockIdx.x < 128) {
            const int row = blockIdx.x * 16 + warp * LR;
            const uint32_t* xr = (const uint32_t*)(P.x + (size_t)row * DM);
            uint32_t v[7 * LR];
#pragma unroll
            for (int i = 0; i < 7 * LR; i++) v[i] = __ldg(xr + lane + 32 * i);
            float sum[LR], sq[LR];
#pragma unroll
            for (int r = 0; r < LR; r++) { sum[r] = 0.f; sq[r] = 0.f; }
#pragma unroll
            for (int i = 0; i < 7 * LR; i++) sum[i / 7] += bf_lo(v[i]) + bf_hi(v[i]);
#pragma unroll
            for (int o = 16; o > 0; o >>= 1)
#pragma unroll
                for (int r = 0; r < LR; r++) sum[r] += __shfl_xor_sync(0xffffffffu, sum[r], o);
#pragma unroll
            for (int r = 0; r < LR; r++) sum[r] *= (1.0f / DM);
#pragma unroll
            for (int i = 0; i < 7 * LR; i++) {
                float d0 = bf_lo(v[i]) - sum[i / 7], d1 = bf_hi(v[i]) - sum[i / 7];
                sq[i / 7] += d0 * d0 + d1 * d1;
            }
#pragma unroll
            for (int o = 16; o > 0; o >>= 1)
#pragma unroll
                for (int r = 0; r < LR; r++) sq[r] += __shfl_xor_sync(0xffffffffu, sq[r], o);
#pragma unroll
            for (int r = 0; r < LR; r++) {
                sum[r] = bf16r(sum[r]);
                sq[r] = rcp(bf16r(sqrt_approx(bf16r(bf16r(sq[r] * (1.0f / DM)) + 1e-5f))));
            }
            uint32_t* yr = (uint32_t*)(g_xn + (size_t)row * DM);
#pragma unroll
            for (int i = 0; i < 7 * LR; i++) {
                float d0 = bf_lo(v[i]) - sum[i / 7], d1 = bf_hi(v[i]) - sum[i / 7];
                bf16r2(d0, d1);
                yr[lane + 32 * i] = pack_bf16(d0 * sq[i / 7], d1 * sq[i / 7]);
            }
            __syncwarp();
            if (lane == 0) asm volatile("mbarrier.arrive.shared::cta.b64 _, [%0];" ::"r"(done_bar + 8) : "memory");
        }
        float acc[128];
        for (int it = 0; it < MAXITEMS; it++) {
            const uint32_t item = P.sched[cl][it];
            const int type = (item >> 12) & 7, ia = (item >> 6) & 63, ib = item & 63;
            if (type == IT_END) break;
            if (!(SALT & 1)) c.ring.uniform();
            const int nk = type == IT_KV ? DC / 64 : type == IT_DN ? FF / 64 : DM / 64;
            if (type == IT_DN && ib == 1) {
                gemm_mainloop<192>(c, acc, nk, 0);
#pragma unroll
                for (int i = 96; i < 128; i++) acc[i] = 0.f;
            }
            else gemm_mainloop<256>(c, acc, nk, type == IT_AT);

            if (type == IT_GU) {
                const Stager st(c);
                c.stage_acquire<0>();
#pragma unroll
                for (int j = 0; j < 8; j++) {
                    uint32_t r[4];
#pragma unroll
                    for (int t = 0; t < 4; t++) {
                        const float h0 = 0.5f * acc[j * 8 + t * 2], h1 = 0.5f * acc[j * 8 + t * 2 + 1];
                        const float w0 = h0 * acc[64 + j * 8 + t * 2], w1 = h1 * acc[64 + j * 8 + t * 2 + 1];
                        r[t] = pack_bf16(fmaf(w0, tanh_hw(h0), w0), fmaf(w1, tanh_hw(h1), w1));
                    }
                    st.put(j >> 2, j & 3, r[0], r[1], r[2], r[3]);
                }
                c.stage_commit<0>();
                continue;
            }
            stage_plain<128, 0, 0>(c, acc);
            if (type != IT_AT) c.stage_commit<0>();
            if (type == IT_AT && c.wg == 0) {
#pragma unroll
                for (int t = 0; t < 2; t++) { uint32_t s = c.wait_full(); c.release(s); }
            }
            stage_plain<128, 64, 1>(c, acc);
            if (type != IT_AT) {
                c.stage_commit<1>();
                continue;
            }
            fence_async_smem();
            c.wg_bar();

            {
                const int m = ia;
                const int grp = (c.wg == 0) ? (int)rank : 3 - (int)rank;
                float m0, m1, l0, l1;
                if (!(SALT & 2)) c.ring.uniform();
                const bool w0 = c.wg == 0;
                if (w0) {
#pragma unroll
                    for (int t = 0; t < 2; t++) { uint32_t s = c.wait_full(); c.release(s); }
                }
                if (grp & 1) attn_step<128, 2>(c, acc, m0, m1, l0, l1, false, w0, false);
                else attn_step<64, 1>(c, acc, m0, m1, l0, l1, false, w0, false);
                for (int j = 2 * m + c.wg; j > 0; j--) attn_step<128, 0>(c, acc, m0, m1, l0, l1, true, w0, !w0 && j != 1);

                l0 += __shfl_xor_sync(0xffffffffu, l0, 1);
                l1 += __shfl_xor_sync(0xffffffffu, l1, 1);
                l0 += __shfl_xor_sync(0xffffffffu, l0, 2);
                l1 += __shfl_xor_sync(0xffffffffu, l1, 2);
                const float i0 = rcp(l0), i1 = rcp(l1);
                uint32_t a[64];
#pragma unroll
                for (int i = 0; i < 32; i++) {
                    a[i * 2 + 0] = pack_bf16(acc[i * 4 + 0] * i0, acc[i * 4 + 1] * i0);
                    a[i * 2 + 1] = pack_bf16(acc[i * 4 + 2] * i1, acc[i * 4 + 3] * i1);
                }
                uint4* cx = g_ctx + (size_t)((ib & 7) * 32 + m * 4 + grp) * 2048 + (fresh_tid() & 127);
                if (ib < 8) {
#pragma unroll
                    for (int i = 0; i < 16; i++) __stcg(cx + i * 128, make_uint4(a[i * 4], a[i * 4 + 1], a[i * 4 + 2], a[i * 4 + 3]));
                    c.stage_acquire<0>();
                    c.stage_commit<0, false>();
                }
                if (ib < 8) continue;
                uint32_t b[64];
#pragma unroll
                for (int i = 0; i < 16; i++) {
                    const uint4 v = __ldcg(cx + i * 128);
                    b[i * 4] = v.x; b[i * 4 + 1] = v.y; b[i * 4 + 2] = v.z; b[i * 4 + 3] = v.w;
                }
                uint32_t sp = oproj_chunk<0>(c, acc, a, b, 0);
                sp = oproj_chunk<1>(c, acc, a, b, sp);
                sp = oproj_chunk<2>(c, acc, a, b, sp);
                sp = oproj_chunk<3>(c, acc, a, b, sp);
                sp = oproj_chunk<4>(c, acc, a, b, sp);
                sp = oproj_chunk<5>(c, acc, a, b, sp);
                sp = oproj_chunk<6>(c, acc, a, b, sp);
                wg_wait<0>();
                c.release(sp);
                stage_plain<64, 0, 0>(c, acc);
                c.stage_commit<0>();
                if (!(SALT & 4)) c.ring.uniform();
#pragma unroll 1
                for (int u = 0; u < 7; u++) {
                    finalize_slot(c, P, m * 256 + ((ib - 8) * 2 + rank) * 16, u);
                }
            }
        }
        lane = fresh_tid() & 31;
        __syncwarp();
        if (lane == 0) asm volatile("mbarrier.arrive.shared::cta.b64 _, [%0];" ::"r"(done_bar) : "memory");
        if (cl >= 64) cluster_sync_relaxed();
        if (threadIdx.x == 0) atomicAdd(&g_cnt[CNT_DONE], 1);
    }
}

typedef CUresult (*PFN_encodeTiled_t)(CUtensorMap*, CUtensorMapDataType, cuuint32_t, void*, const cuuint64_t*, const cuuint64_t*,
                                      const cuuint32_t*, const cuuint32_t*, CUtensorMapInterleave, CUtensorMapSwizzle,
                                      CUtensorMapL2promotion, CUtensorMapFloatOOBfill);

static void make_map(PFN_encodeTiled_t enc, CUtensorMap* m, const void* ptr, uint64_t rows, uint64_t cols, uint32_t box_rows, uint32_t box_blk) {
    cuuint64_t dims[3] = {64, rows, cols / 64};
    cuuint64_t strides[2] = {cols * 2, 128};
    cuuint32_t box[3] = {64, box_rows, box_blk};
    cuuint32_t es[3] = {1, 1, 1};
    enc(m, CU_TENSOR_MAP_DATA_TYPE_BFLOAT16, 3, const_cast<void*>(ptr), dims, strides, box, es, CU_TENSOR_MAP_INTERLEAVE_NONE,
        CU_TENSOR_MAP_SWIZZLE_128B, CU_TENSOR_MAP_L2_PROMOTION_L2_128B, CU_TENSOR_MAP_FLOAT_OOB_FILL_NONE);
}

static void make_map_fin(PFN_encodeTiled_t enc, CUtensorMap* m, const void* ptr, uint32_t planes) {
    cuuint64_t dims[3] = {DM, SEQ, planes};
    cuuint64_t strides[2] = {DM * 2, (cuuint64_t)SEQ * DM * 2};
    cuuint32_t box[3] = {64, 16, planes};
    cuuint32_t es[3] = {1, 1, 1};
    enc(m, CU_TENSOR_MAP_DATA_TYPE_BFLOAT16, 3, const_cast<void*>(ptr), dims, strides, box, es, CU_TENSOR_MAP_INTERLEAVE_NONE,
        CU_TENSOR_MAP_SWIZZLE_NONE, CU_TENSOR_MAP_L2_PROMOTION_NONE, CU_TENSOR_MAP_FLOAT_OOB_FILL_NONE);
}

static void build_schedule(Params& P) {
    int n[NCLUSTER];
    for (int c = 0; c < NCLUSTER; c++) {
        n[c] = 0;
        for (int i = 0; i < MAXITEMS; i++) P.sched[c][i] = 0;
    }
    auto push = [&](int c, int type, int a, int b) { P.sched[c][n[c]++] = (uint16_t)((type << 12) | (a << 6) | b); };
    auto kv1 = [&](int c, int t) { push(c, IT_KV, t % 8, (t / 16) + 16 * ((t / 8) & 1)); };
    const int sb0 = 35, sb1 = 44;
    for (int c = 0; c < 64; c++) {
        const int m = c % 8, hp = c / 8;
        const bool sb = c == sb0 || c == sb1;
        if (!sb) kv1(c, c);
        if (hp >= 4) { kv1(c, 64 + (c - 32)); kv1(c, 96 + (c - 32)); }
        if (sb) { push(c, IT_GU, 0, 0); push(c, IT_GU, 0, 0); }
        push(c, IT_AT, m, hp);
        if (hp < 4 && m <= 5) for (int r = 0; r < 4; r++) push(c, IT_GU, 0, 0);
        push(c, IT_KV, 7 - m, 8 + hp); push(c, IT_KV, 7 - m, 24 + hp);
        if (hp < 4 && m >= 6) push(c, IT_DN, (m - 6) * 4 + hp, 0);
        push(c, IT_AT, 7 - m, 8 + hp);
        if (m == 0) for (int i = 1; i <= 3; i++) P.sched[c][n[c] - i] |= 0x8000;
    }
    for (int e = 0; e < 2; e++) {
        kv1(64 + e, e ? sb1 : sb0);
        for (int i = 0; i < 6; i++) push(64 + e, IT_GU, 0, 0);
        for (int i = 0; i < 4; i++) push(64 + e, IT_DN, i * 2 + e, 1);
    }
    int tc[112], ti[112], tt[112], ng = 0;
    for (int c = 0; c < NCLUSTER; c++) {
        int t = 3;
        for (int i = 0; i < n[c]; i++) {
            const int ty = (P.sched[c][i] >> 12) & 7, a = (P.sched[c][i] >> 6) & 63;
            t += ty == IT_KV ? 18 : ty == IT_GU ? 9 : ty == IT_DN ? 29 : 16 + a * 17 / 2;
            if (ty == IT_GU) { tc[ng] = c; ti[ng] = i; tt[ng] = t; ng++; }
        }
    }
    for (int g = 0; g < ng; g++) {
        int rk = 0;
        for (int o = 0; o < ng; o++) rk += tt[o] < tt[g] || (tt[o] == tt[g] && o < g);
        P.sched[tc[g]][ti[g]] = (uint16_t)((IT_GU << 12) | ((rk / 14) << 6) | (rk % 14));
    }
}

extern "C" void kernel_launch(void* const* d_in, const int* in_sizes, int n_in, void* d_out, int out_size) {
    static Params P;
    static bool init = false;
    static const void* cached[11];
    bool same = init;
    for (int i = 0; i < 10 && same; i++) same = cached[i] == d_in[i];
    same = same && cached[10] == d_out;
    if (!same) {
        void* fn = nullptr;
        cudaDriverEntryPointQueryResult qres;
        cudaGetDriverEntryPoint("cuTensorMapEncodeTiled", &fn, cudaEnableDefault, &qres);
        PFN_encodeTiled_t enc = (PFN_encodeTiled_t)fn;
        void *xn, *kv, *h, *sg, *part;
        cudaGetSymbolAddress(&xn, g_xn);
        cudaGetSymbolAddress(&kv, g_kv);
        cudaGetSymbolAddress(&h, g_h);
        cudaGetSymbolAddress(&sg, g_sg);
        cudaGetSymbolAddress(&part, g_part);
        make_map(enc, &P.ckv, d_in[1], SEQ, DC, 64, 2);
        make_map(enc, &P.wq, d_in[2], DM, NH * HD, 64, 2);
        make_map(enc, &P.wuk, d_in[3], DC, NH * HD, 64, 2);
        make_map(enc, &P.wuv, d_in[4], DC, NH * HD, 64, 2);
        make_map(enc, &P.wo, d_in[5], NH * HD, DM, 128, 1);
        make_map(enc, &P.wg, d_in[7], DM, FF, 64, 2);
        make_map(enc, &P.wu, d_in[8], DM, FF, 64, 2);
        make_map(enc, &P.wd, d_in[9], FF, DM, 64, 2);
        make_map(enc, &P.xn, xn, SEQ, DM, 64, 2);
        make_map(enc, &P.k_ld, kv, SEQ, 2 * NH * HD, 128, 1);
        make_map(enc, &P.v_ld, kv, SEQ, 2 * NH * HD, 64, 2);
        make_map(enc, &P.h, h, SEQ, FF, 64, 2);
        make_map(enc, &P.sg_st, sg, SEQ, DM, 64, 2);
        make_map(enc, &P.p_st, part, (uint64_t)(NH / 2) * SEQ, DM, 64, 1);
        make_map_fin(enc, &P.p_ld, part, NH / 2);
        make_map_fin(enc, &P.x_ld, d_in[0], 1);
        make_map_fin(enc, &P.g_ld, sg, 1);
        P.x = (const bf16*)d_in[0];
        P.pwq = (const bf16*)d_in[2]; P.pwuk = (const bf16*)d_in[3]; P.pwuv = (const bf16*)d_in[4];
        P.out = (bf16*)d_out;
        build_schedule(P);
        cudaFuncSetAttribute(fused_kernel, cudaFuncAttributeMaxDynamicSharedMemorySize, SMEM_BYTES);
        for (int i = 0; i < 10; i++) cached[i] = d_in[i];
        cached[10] = d_out;
        init = true;
    }
    fused_kernel<<<NCTA, 384, SMEM_BYTES>>>(P);
}
```
